```python
import torch

def _softmax(x, axis=-1):
    return torch.softmax(x, dim=axis)
def _gelu(x):
    return torch.nn.functional.gelu(x, approximate="tanh")
def _silu(x):
    return torch.nn.functional.silu(x)
def _sigmoid(x):
    return torch.sigmoid(x)
def _layernorm(x, axis=-1, eps=1e-5):
    m = x.mean(dim=axis, keepdim=True)
    v = x.var(dim=axis, keepdim=True, unbiased=False)
    return (x - m) / torch.sqrt(v + eps)
def _scatter_add(tgt, idx, src, axis=0):
    return tgt.clone().index_add_(axis, idx, src)
def _segment_sum(src, seg, n):
    out = torch.zeros((n,) + src.shape[1:], dtype=src.dtype)
    return out.index_add_(0, seg, src)
def _pad(x, pw):
    flat = tuple(v for pair in reversed(pw) for v in pair)
    return torch.nn.functional.pad(x, flat)

kernel_name = 'standalone__detection_seg_fpn_lateral__vision'

def setup_inputs():

    _w = (lambda a: (lambda t: t.to(torch.bfloat16) if t.is_floating_point() else t)(torch.as_tensor(a)))
    H = W = (512 // 2) * 2
    C = 96
    k = 3
    return {
        "c_fine": _w((lambda *s: torch.randn(*s, dtype=torch.bfloat16) * 0.05)(1, H, W, C)),
        "p_coarse": _w((lambda *s: torch.randn(*s, dtype=torch.bfloat16) * 0.05)(1, H // 2, W // 2, C)),
        "w_lat": _w((lambda *s: torch.randn(*s, dtype=torch.bfloat16) * 0.05)(C, C)),
        "w_out": _w((lambda *s: torch.randn(*s, dtype=torch.bfloat16) * 0.05)(k, k, C, C)),
    }

def reference(c_fine, p_coarse, w_lat, w_out):
    B, H, W, C = c_fine.shape
    k = 3
    lat = torch.einsum("bhwc,cd->bhwd", c_fine, w_lat)
    up = (lambda x, n, axis: torch.repeat_interleave(x, n, dim=axis))((lambda x, n, axis: torch.repeat_interleave(x, n, dim=axis))(p_coarse, 2, axis=1), 2, axis=2)
    m = lat + up
    pad = k // 2
    mp = _pad(m, ((0, 0), (pad, pad), (pad, pad), (0, 0)))
    o = None
    for di in range(k):
        for dj in range(k):
            t = torch.einsum("bhwc,cd->bhwd", mp[:, di:di + H, dj:dj + W, :], w_out[di, dj])
            o = t if o is None else o + t
    return o
```

```cpp
#include <cuda_runtime.h>
#include <cuda_bf16.h>
#include <stdint.h>

namespace {

constexpr int IMG = 512;
constexpr int P = 67;
constexpr int PLANE = P * 16;
constexpr int TPOS = 6 * PLANE;
constexpr int T_BYTES = 4 * TPOS;
constexpr int UT = 9216;
constexpr int OFF_U = 0;
constexpr int OFF_WL = 12 * UT;
constexpr int OFF_T = OFF_WL + 9216;
constexpr int OFF_X = OFF_T + 2 * T_BYTES;
constexpr int X_BYTES = 12288;
constexpr int OFF_H = OFF_X + 2 * X_BYTES;
constexpr int HSIDE = 36 * 96;
constexpr int H_BYTES = 2 * HSIDE;
constexpr int OFF_BAR = OFF_H + 2 * H_BYTES;
constexpr int SMEM_BYTES = OFF_BAR + 64;
constexpr int NSTEP = 16;

#define R4(a, o) "+f"(a[o]), "+f"(a[o + 1]), "+f"(a[o + 2]), "+f"(a[o + 3])
#define R8(a, o) R4(a, o), R4(a, o + 4)
#define R24(a, o) R8(a, o), R8(a, o + 8), R8(a, o + 16)

__device__ __forceinline__ void wgmma_ss_n96(float (&d)[48], uint64_t da, uint64_t db, int scaleD) {
  asm volatile(
      "{\n.reg .pred p;\nsetp.ne.b32 p, %50, 0;\n"
      "wgmma.mma_async.sync.aligned.m64n96k16.f32.bf16.bf16 "
      "{%0, %1, %2, %3, %4, %5, %6, %7, %8, %9, %10, %11, %12, %13, %14, %15, %16, %17, %18, %19, %20, %21, %22, %23, "
      "%24, %25, %26, %27, %28, %29, %30, %31, %32, %33, %34, %35, %36, %37, %38, %39, %40, %41, %42, %43, %44, %45, %46, %47}, "
      "%48, %49, p, 1, 1, 0, 0;\n}\n"
      : R24(d, 0), R24(d, 24)
      : "l"(da), "l"(db), "r"(scaleD));
}
__device__ __forceinline__ void wgmma_rs_n48(float (&d)[24], uint32_t a0, uint32_t a1, uint32_t a2, uint32_t a3,
                                             uint64_t db, int scaleD) {
  asm volatile(
      "{\n.reg .pred p;\nsetp.ne.b32 p, %29, 0;\n"
      "wgmma.mma_async.sync.aligned.m64n48k16.f32.bf16.bf16 "
      "{%0, %1, %2, %3, %4, %5, %6, %7, %8, %9, %10, %11, %12, %13, %14, %15, %16, %17, %18, %19, %20, %21, %22, %23}, "
      "{%24, %25, %26, %27}, %28, p, 1, 1, 0;\n}\n"
      : R24(d, 0)
      : "r"(a0), "r"(a1), "r"(a2), "r"(a3), "l"(db), "r"(scaleD));
}
__device__ __forceinline__ void wg_fence() { asm volatile("wgmma.fence.sync.aligned;" ::: "memory"); }
__device__ __forceinline__ void wg_commit() { asm volatile("wgmma.commit_group.sync.aligned;" ::: "memory"); }
template <int N>
__device__ __forceinline__ void wg_wait() {
  asm volatile("wgmma.wait_group.sync.aligned %0;" ::"n"(N) : "memory");
}
template <int N>
__device__ __forceinline__ void fence_regs(float (&a)[N]) {
#pragma unroll
  for (int i = 0; i < N; i++) asm volatile("" : "+f"(a[i])::"memory");
}
__device__ __forceinline__ uint64_t make_desc(uint32_t saddr, uint32_t lbo, uint32_t sbo) {
  return (uint64_t)((saddr & 0x3FFFF) >> 4) | ((uint64_t)(lbo >> 4) << 16) | ((uint64_t)(sbo >> 4) << 32);
}
__device__ __forceinline__ void fence_async_smem() { asm volatile("fence.proxy.async.shared::cta;" ::: "memory"); }
__device__ __forceinline__ void bar_wg(int id) { asm volatile("bar.sync %0, 128;" ::"r"(id) : "memory"); }

__device__ __forceinline__ uint32_t pack_bf16(float lo, float hi) {
  uint32_t r;
  asm("cvt.rn.bf16x2.f32 %0, %1, %2;" : "=r"(r) : "f"(hi), "f"(lo));
  return r;
}
__device__ __forceinline__ uint32_t hadd2(uint32_t a, uint32_t b) {
  uint32_t r;
  asm("add.rn.bf16x2 %0, %1, %2;" : "=r"(r) : "r"(a), "r"(b));
  return r;
}
__device__ __forceinline__ uint32_t hsub2(uint32_t a, uint32_t b) {
  uint32_t r;
  asm("sub.rn.bf16x2 %0, %1, %2;" : "=r"(r) : "r"(a), "r"(b));
  return r;
}
__device__ __forceinline__ uint32_t hfma2(uint32_t a, uint32_t b, uint32_t c) {
  uint32_t r;
  asm("fma.rn.bf16x2 %0, %1, %2, %3;" : "=r"(r) : "r"(a), "r"(b), "r"(c));
  return r;
}
__device__ __forceinline__ float bf_lo(uint32_t a) { return __uint_as_float(a << 16); }
__device__ __forceinline__ float bf_hi(uint32_t a) { return __uint_as_float(a & 0xffff0000u); }

__device__ __forceinline__ uint4 ldg128(const void* p) {
  uint4 v;
  asm volatile("ld.global.nc.L1::no_allocate.v4.u32 {%0,%1,%2,%3}, [%4];"
               : "=r"(v.x), "=r"(v.y), "=r"(v.z), "=r"(v.w)
               : "l"(p));
  return v;
}
__device__ __forceinline__ uint2 ldg64(const void* p) {
  uint2 v;
  asm volatile("ld.global.nc.L1::no_allocate.v2.u32 {%0,%1}, [%2];" : "=r"(v.x), "=r"(v.y) : "l"(p));
  return v;
}
__device__ __forceinline__ void sts64(uint32_t a, uint32_t x, uint32_t y) {
  asm volatile("st.shared.v2.u32 [%0], {%1,%2};" ::"r"(a), "r"(x), "r"(y) : "memory");
}
__device__ __forceinline__ void sts128(uint32_t a, uint32_t x, uint32_t y, uint32_t z, uint32_t w) {
  asm volatile("st.shared.v4.u32 [%0], {%1,%2,%3,%4};" ::"r"(a), "r"(x), "r"(y), "r"(z), "r"(w) : "memory");
}
__device__ __forceinline__ uint4 lds128(uint32_t a) {
  uint4 v;
  asm volatile("ld.shared.v4.u32 {%0,%1,%2,%3}, [%4];" : "=r"(v.x), "=r"(v.y), "=r"(v.z), "=r"(v.w) : "r"(a) : "memory");
  return v;
}
__device__ __forceinline__ void mbar_init(uint32_t bar, uint32_t cnt) {
  asm volatile("mbarrier.init.shared::cta.b64 [%0], %1;" ::"r"(bar), "r"(cnt) : "memory");
}
__device__ __forceinline__ void mbar_expect_tx(uint32_t bar, uint32_t bytes) {
  asm volatile("mbarrier.arrive.expect_tx.shared::cta.b64 _, [%0], %1;" ::"r"(bar), "r"(bytes) : "memory");
}
__device__ __forceinline__ void mbar_wait_cluster(uint32_t bar, uint32_t parity) {
  uint32_t ok;
  int it = 0;
  do {
    asm volatile(
        "{\n.reg .pred p;\n"
        "mbarrier.try_wait.parity.acquire.cluster.shared::cta.b64 p, [%1], %2;\n"
        "selp.u32 %0, 1, 0, p;\n}\n"
        : "=r"(ok)
        : "r"(bar), "r"(parity)
        : "memory");
    if (++it > (1 << 22)) __trap();
  } while (!ok);
}
__device__ __forceinline__ void mbar_arrive_remote(uint32_t rbar) {
  asm volatile("mbarrier.arrive.release.cluster.shared::cluster.b64 _, [%0];" ::"r"(rbar) : "memory");
}
__device__ __forceinline__ uint32_t mapa(uint32_t a, uint32_t rank) {
  uint32_t r;
  asm("mapa.shared::cluster.u32 %0, %1, %2;" : "=r"(r) : "r"(a), "r"(rank));
  return r;
}
__device__ __forceinline__ void st_async128(uint32_t ra, uint32_t x, uint32_t y, uint32_t z, uint32_t w, uint32_t rbar) {
  asm volatile("st.async.weak.shared::cluster.mbarrier::complete_tx::bytes.v4.b32 [%0], {%1,%2,%3,%4}, [%5];" ::"r"(ra),
               "r"(x), "r"(y), "r"(z), "r"(w), "r"(rbar)
               : "memory");
}
__device__ __forceinline__ void cluster_arrive() { asm volatile("barrier.cluster.arrive.release.aligned;" ::: "memory"); }
__device__ __forceinline__ void cluster_wait() { asm volatile("barrier.cluster.wait.acquire.aligned;" ::: "memory"); }

__device__ __forceinline__ uint32_t wsel(const uint4& v, int i) { return i == 0 ? v.x : i == 1 ? v.y : i == 2 ? v.z : v.w; }

struct CFrag {
  uint4 v[2][3];
};

__device__ __forceinline__ void lateral_issue(float (&acc)[24], const CFrag& c, uint64_t dwl) {
#pragma unroll
  for (int i = 0; i < 3; i++) {
    wgmma_rs_n48(acc, c.v[0][i].x, c.v[1][i].x, c.v[0][i].y, c.v[1][i].y, dwl + (uint64_t)((2 * i) * 1536 >> 4), i != 0);
    wgmma_rs_n48(acc, c.v[0][i].z, c.v[1][i].z, c.v[0][i].w, c.v[1][i].w, dwl + (uint64_t)((2 * i + 1) * 1536 >> 4), 1);
  }
}
__device__ __forceinline__ void lateral_finish(const float (&acc)[24], const uint2 (&p)[3], uint32_t (&d)[12]) {
#pragma unroll
  for (int h = 0; h < 2; h++)
#pragma unroll
    for (int jj = 0; jj < 3; jj++) {
      d[h * 6 + jj * 2 + 0] = hadd2(pack_bf16(acc[4 * (2 * jj) + 2 * h], acc[4 * (2 * jj) + 2 * h + 1]), p[jj].x);
      d[h * 6 + jj * 2 + 1] = hadd2(pack_bf16(acc[4 * (2 * jj + 1) + 2 * h], acc[4 * (2 * jj + 1) + 2 * h + 1]), p[jj].y);
    }
}

__global__ void __cluster_dims__(2, 1, 1) __launch_bounds__(256, 1)
    fpn_kernel(const __nv_bfloat16* __restrict__ c_fine, const __nv_bfloat16* __restrict__ p_coarse,
               const __nv_bfloat16* __restrict__ w_lat, const __nv_bfloat16* __restrict__ w_out,
               __nv_bfloat16* __restrict__ out) {
  extern __shared__ __align__(1024) unsigned char smem[];
  const uint32_t sb = (uint32_t)__cvta_generic_to_shared(smem);
  const int tid = threadIdx.x;
  const int wg = tid >> 7;
  const int t128 = tid & 127;
  const int w = (tid >> 5) & 3;
  const int lane = tid & 31;
  const int g = lane >> 2, q = lane & 3;
  uint32_t rank;
  asm("mov.u32 %0, %%cluster_ctarank;" : "=r"(rank));
  const int cl = blockIdx.x >> 1;
  const int y0 = (cl >> 2) * 32;
  const int x0 = ((cl & 3) * 2 + wg) * 64;

  const uint32_t bar_full = sb + OFF_BAR + wg * 16;
  const uint32_t bar_empty = bar_full + 8;
  if (tid == 0) {
    mbar_init(sb + OFF_BAR + 0, 1);
    mbar_init(sb + OFF_BAR + 8, 4);
    mbar_init(sb + OFF_BAR + 16, 1);
    mbar_init(sb + OFF_BAR + 24, 4);
    asm volatile("fence.mbarrier_init.release.cluster;" ::: "memory");
  }
  cluster_arrive();

  const unsigned char* cf = (const unsigned char*)c_fine;
  const unsigned char* pc = (const unsigned char*)p_coarse;

  CFrag ca, cb;
  uint2 pa[3], pb[3];
  const int hrow = 16 * w + 2 * g;
  {
    const int xl = max(x0 - 1, 0), xr = min(x0 + 64, IMG - 1);
#pragma unroll
    for (int h = 0; h < 2; h++) {
      const int yy = min(max(y0 - 2 + hrow + h, 0), IMG - 1);
#pragma unroll
      for (int i = 0; i < 3; i++) {
        ca.v[h][i] = ldg128(cf + ((size_t)yy * IMG + xl) * 192 + 64 * i + 16 * q);
        cb.v[h][i] = ldg128(cf + ((size_t)yy * IMG + xr) * 192 + 64 * i + 16 * q);
      }
    }
    const int py = min(max((y0 >> 1) - 1 + 8 * w + g, 0), 255);
#pragma unroll
    for (int jj = 0; jj < 3; jj++) {
      pa[jj] = ldg64(pc + ((size_t)py * 256 + (xl >> 1)) * 192 + 96 * rank + 32 * jj + 8 * q);
      pb[jj] = ldg64(pc + ((size_t)py * 256 + (xr >> 1)) * 192 + 96 * rank + 32 * jj + 8 * q);
    }
  }

  if (tid < 216) {
    const int dj = tid / 72, rem = tid % 72, kc = rem / 12, u = rem % 12;
    const unsigned char* src = (const unsigned char*)w_out + ((size_t)(dj * 96 + 48 * rank + 8 * kc) * 96 + 8 * u) * 2;
    uint4 v[3][8];
#pragma unroll
    for (int di = 0; di < 3; di++)
#pragma unroll
      for (int kk = 0; kk < 8; kk++) v[di][kk] = ldg128(src + (size_t)di * 3 * 96 * 192 + kk * 192);
    const uint32_t base = sb + OFF_U + dj * UT + kc * 1536 + (8 * (4 * (u >> 2)) + 2 * (u & 3)) * 16;
    const uint32_t o0 = rank ? 9 * UT : 0, o3 = rank ? 0 : 9 * UT;
    const float sg = rank ? -0.5f : 0.5f;
#pragma unroll
    for (int wd = 0; wd < 4; wd++) {
      uint32_t u0[2][4], u1[2][4], u2[2][4], u3[2][4];
#pragma unroll
      for (int kp = 0; kp < 4; kp++) {
        const uint32_t a0 = wsel(v[0][2 * kp], wd), a1 = wsel(v[0][2 * kp + 1], wd);
        const uint32_t b0 = wsel(v[1][2 * kp], wd), b1 = wsel(v[1][2 * kp + 1], wd);
        const uint32_t c0 = wsel(v[2][2 * kp], wd), c1 = wsel(v[2][2 * kp + 1], wd);
        u0[0][kp] = __byte_perm(a0, a1, 0x5410);
        u0[1][kp] = __byte_perm(a0, a1, 0x7632);
        u3[0][kp] = __byte_perm(c0, c1, 0x5410);
        u3[1][kp] = __byte_perm(c0, c1, 0x7632);
        const float s0l = bf_lo(a0) + bf_lo(c0), s1l = bf_lo(a1) + bf_lo(c1);
        const float s0h = bf_hi(a0) + bf_hi(c0), s1h = bf_hi(a1) + bf_hi(c1);
        u1[0][kp] = pack_bf16((s0l + bf_lo(b0)) * 0.5f, (s1l + bf_lo(b1)) * 0.5f);
        u1[1][kp] = pack_bf16((s0h + bf_hi(b0)) * 0.5f, (s1h + bf_hi(b1)) * 0.5f);
        u2[0][kp] = pack_bf16((s0l - bf_lo(b0)) * sg, (s1l - bf_lo(b1)) * sg);
        u2[1][kp] = pack_bf16((s0h - bf_hi(b0)) * sg, (s1h - bf_hi(b1)) * sg);
      }
#pragma unroll
      for (int e = 0; e < 2; e++) {
        const uint32_t a = base + (8 * wd + e) * 16;
        sts128(a + o0, u0[e][0], u0[e][1], u0[e][2], u0[e][3]);
        sts128(a + 3 * UT, u1[e][0], u1[e][1], u1[e][2], u1[e][3]);
        sts128(a + 6 * UT, u2[e][0], u2[e][1], u2[e][2], u2[e][3]);
        sts128(a + o3, u3[e][0], u3[e][1], u3[e][2], u3[e][3]);
      }
    }
  } else {
    for (int blk = tid - 216; blk < 72; blk += 40) {
      const int kc = blk / 6, u = blk % 6;
      const int i = kc >> 2, b = (kc >> 1) & 1, c = kc & 1;
      uint4 v[8];
#pragma unroll
      for (int kk = 0; kk < 8; kk++) {
        const int ch = 32 * i + 8 * (kk >> 1) + 4 * b + 2 * c + (kk & 1);
        v[kk] = ldg128((const unsigned char*)w_lat + ((size_t)ch * 96 + 48 * rank + 8 * u) * 2);
      }
      const int jj = u >> 1;
#pragma unroll
      for (int wd = 0; wd < 4; wd++) {
        const int qq = 2 * (u & 1) + (wd >> 1), jo = wd & 1;
        const uint32_t a = sb + OFF_WL + kc * 768 + (8 * (2 * jj + jo) + 2 * qq) * 16;
        uint32_t lo[4], hi[4];
#pragma unroll
        for (int kp = 0; kp < 4; kp++) {
          lo[kp] = __byte_perm(wsel(v[2 * kp], wd), wsel(v[2 * kp + 1], wd), 0x5410);
          hi[kp] = __byte_perm(wsel(v[2 * kp], wd), wsel(v[2 * kp + 1], wd), 0x7632);
        }
        sts128(a, lo[0], lo[1], lo[2], lo[3]);
        sts128(a + 16, hi[0], hi[1], hi[2], hi[3]);
      }
    }
  }
  fence_async_smem();
  __syncthreads();

  const uint64_t dwl = make_desc(sb + OFF_WL, 768, 128);
  const uint32_t tb = sb + OFF_T + wg * T_BYTES;
  const uint64_t dA = make_desc(tb, PLANE, 128);
  const uint64_t dB = make_desc(sb + OFF_U, 1536, 128);
  const uint32_t hb = sb + OFF_H + wg * H_BYTES;
  const uint32_t xb = sb + OFF_X + wg * X_BYTES + t128 * 16;
  const uint32_t peer = rank ^ 1;
  const uint32_t r_xb = mapa(xb, peer);
  const uint32_t r_full = mapa(bar_full, peer);
  const uint32_t r_empty = mapa(bar_empty, peer);

  const int pxl = 16 * w + 2 * g;
  const unsigned char* cptr = cf + ((size_t)x0 + pxl) * 192 + 16 * q;
  const unsigned char* pptr = pc + ((size_t)(x0 >> 1) + 8 * w + g) * 192 + 96 * rank + 8 * q;

  uint32_t d0[12], d1[12], d2[12], d3[12];
  float la[24], lb[24];

  wg_fence();
  lateral_issue(la, ca, dwl);
  lateral_issue(lb, cb, dwl);
  wg_commit();
  wg_wait<0>();
  fence_regs(la);
  fence_regs(lb);
  lateral_finish(la, pa, d0);
  lateral_finish(lb, pb, d1);
  {
    const int ra = max(y0 - 1, 0), rb = y0;
#pragma unroll
    for (int h = 0; h < 2; h++)
#pragma unroll
      for (int i = 0; i < 3; i++) {
        ca.v[h][i] = ldg128(cptr + (size_t)ra * 98304 + h * 192 + 64 * i);
        cb.v[h][i] = ldg128(cptr + (size_t)rb * 98304 + h * 192 + 64 * i);
      }
#pragma unroll
    for (int jj = 0; jj < 3; jj++) {
      pa[jj] = ldg64(pptr + (size_t)(ra >> 1) * 49152 + 32 * jj);
      pb[jj] = ldg64(pptr + (size_t)(rb >> 1) * 49152 + 32 * jj);
    }
  }
  if (hrow < 36) {
#pragma unroll
    for (int h = 0; h < 2; h++) {
      const int yy = y0 - 2 + hrow + h;
      const bool rv = yy >= 0 && yy < IMG;
      const bool lv = rv && x0 > 0, rvv = rv && x0 + 64 < IMG;
#pragma unroll
      for (int jj = 0; jj < 3; jj++) {
        const uint32_t a = hb + (hrow + h) * 96 + 32 * jj + 8 * q;
        sts64(a, lv ? d0[h * 6 + jj * 2] : 0u, lv ? d0[h * 6 + jj * 2 + 1] : 0u);
        sts64(a + HSIDE, rvv ? d1[h * 6 + jj * 2] : 0u, rvv ? d1[h * 6 + jj * 2 + 1] : 0u);
      }
    }
  }

  wg_fence();
  lateral_issue(la, ca, dwl);
  lateral_issue(lb, cb, dwl);
  wg_commit();
  wg_wait<0>();
  fence_regs(la);
  fence_regs(lb);
  lateral_finish(la, pa, d0);
  lateral_finish(lb, pb, d1);
  if (y0 == 0) {
#pragma unroll
    for (int i = 0; i < 12; i++) d0[i] = 0;
  }
  {
#pragma unroll
    for (int h = 0; h < 2; h++)
#pragma unroll
      for (int i = 0; i < 3; i++) {
        ca.v[h][i] = ldg128(cptr + (size_t)(y0 + 1) * 98304 + h * 192 + 64 * i);
        cb.v[h][i] = ldg128(cptr + (size_t)(y0 + 2) * 98304 + h * 192 + 64 * i);
      }
#pragma unroll
    for (int jj = 0; jj < 3; jj++) {
      pa[jj] = pb[jj];
      pb[jj] = ldg64(pptr + (size_t)((y0 >> 1) + 1) * 49152 + 32 * jj);
    }
  }
  cluster_wait();

  const uint32_t ts = tb + (q >> 1) * PLANE + (pxl + 1) * 16 + (q & 1) * 8;
  const uint32_t ts0 = ts + (rank ? 3 * TPOS : 0);
  const uint32_t ts3 = ts + (rank ? 0 : 3 * TPOS);
  const int hside = lane >= 6 ? 1 : 0, hkc = lane - 6 * hside;
  const uint32_t hsrcA = hb + hside * HSIDE + (1 + w) * 96 + hkc * 16;
  const uint32_t hsrcB = hb + hside * HSIDE + (1 + (w < 2 ? 2 : 1)) * 96 + hkc * 16;
  const uint32_t hsgn = (w == 1) ? 0x3f803f80u : 0xbf80bf80u;
  const int hslot = (w == 1 || w == 2) ? w : ((w == 0) != (rank != 0) ? 0 : 3);
  const uint32_t hdst = tb + hslot * TPOS + hkc * PLANE + (hside ? 65 * 16 : 0);

  unsigned char* optr = (unsigned char*)out + (((size_t)(y0 + rank) * IMG) + x0 + 16 * w + g) * 192 + 16 * q;

  float ax[48], ay[48];

#pragma unroll 1
  for (int s = 0; s < NSTEP; s++) {
    const int y = y0 + 2 * s;
    wg_fence();
    lateral_issue(la, ca, dwl);
    lateral_issue(lb, cb, dwl);
    wg_commit();
    wg_wait<0>();
    fence_regs(la);
    fence_regs(lb);
    if (t128 == 0) mbar_expect_tx(bar_full, X_BYTES);
    lateral_finish(la, pa, d2);
    lateral_finish(lb, pb, d3);
    if (y + 2 >= IMG) {
#pragma unroll
      for (int i = 0; i < 12; i++) d3[i] = 0;
    }
    if (s + 1 < NSTEP) {
      const int rb = min(y + 4, IMG - 1);
#pragma unroll
      for (int h = 0; h < 2; h++)
#pragma unroll
        for (int i = 0; i < 3; i++) {
          ca.v[h][i] = ldg128(cptr + (size_t)(y + 3) * 98304 + h * 192 + 64 * i);
          cb.v[h][i] = ldg128(cptr + (size_t)rb * 98304 + h * 192 + 64 * i);
        }
#pragma unroll
      for (int jj = 0; jj < 3; jj++) {
        pa[jj] = pb[jj];
        pb[jj] = ldg64(pptr + (size_t)(rb >> 1) * 49152 + 32 * jj);
      }
    }
    bar_wg(1 + wg);
#pragma unroll
    for (int h = 0; h < 2; h++)
#pragma unroll
      for (int jj = 0; jj < 3; jj++) {
        const int i0 = h * 6 + jj * 2;
        const uint32_t o = 2 * jj * PLANE + h * 16;
        sts64(ts + TPOS + o, hadd2(d1[i0], d2[i0]), hadd2(d1[i0 + 1], d2[i0 + 1]));
        sts64(ts + 2 * TPOS + o, hsub2(d2[i0], d1[i0]), hsub2(d2[i0 + 1], d1[i0 + 1]));
        sts64(ts0 + o, hsub2(d0[i0], d2[i0]), hsub2(d0[i0 + 1], d2[i0 + 1]));
        sts64(ts3 + o, hsub2(d3[i0], d1[i0]), hsub2(d3[i0 + 1], d1[i0 + 1]));
      }
    if (lane < 12) {
      const uint4 a = lds128(hsrcA + s * 192), b = lds128(hsrcB + s * 192);
      sts128(hdst, hfma2(b.x, hsgn, a.x), hfma2(b.y, hsgn, a.y), hfma2(b.z, hsgn, a.z), hfma2(b.w, hsgn, a.w));
    }
#pragma unroll
    for (int i = 0; i < 12; i++) {
      d0[i] = d2[i];
      d1[i] = d3[i];
    }
    fence_async_smem();
    bar_wg(1 + wg);

    wg_fence();
#pragma unroll
    for (int dj = 0; dj < 3; dj++)
#pragma unroll
      for (int ks = 0; ks < 3; ks++) {
        wgmma_ss_n96(ax, dA + (uint64_t)((1 * TPOS + 2 * ks * PLANE + dj * 16) >> 4),
                     dB + (uint64_t)(((3 + dj) * UT + 2 * ks * 1536) >> 4), (dj | ks) != 0);
        wgmma_ss_n96(ay, dA + (uint64_t)((2 * TPOS + 2 * ks * PLANE + dj * 16) >> 4),
                     dB + (uint64_t)(((6 + dj) * UT + 2 * ks * 1536) >> 4), (dj | ks) != 0);
      }
    wg_commit();
    wg_wait<0>();
    fence_regs(ax);
    fence_regs(ay);
    mbar_wait_cluster(bar_empty, (s & 1) ^ 1);
#pragma unroll
    for (int i = 0; i < 48; i++) {
      const float a = ax[i], b = ay[i];
      ax[i] = a + b;
      ay[i] = a - b;
    }
    fence_regs(ax);
    fence_regs(ay);
    wg_fence();
#pragma unroll
    for (int dj = 0; dj < 3; dj++)
#pragma unroll
      for (int ks = 0; ks < 3; ks++)
        wgmma_ss_n96(ay, dA + (uint64_t)((3 * TPOS + 2 * ks * PLANE + dj * 16) >> 4),
                     dB + (uint64_t)(((9 + dj) * UT + 2 * ks * 1536) >> 4), 1);
    wg_commit();
#pragma unroll
    for (int dj = 0; dj < 3; dj++)
#pragma unroll
      for (int ks = 0; ks < 3; ks++)
        wgmma_ss_n96(ax, dA + (uint64_t)((0 * TPOS + 2 * ks * PLANE + dj * 16) >> 4),
                     dB + (uint64_t)(((0 + dj) * UT + 2 * ks * 1536) >> 4), 1);
    wg_commit();
    wg_wait<1>();
    fence_regs(ay);
#pragma unroll
    for (int h = 0; h < 2; h++)
#pragma unroll
      for (int J = 0; J < 3; J++) {
        const int b = 16 * J + 2 * h;
        st_async128(r_xb + (h * 3 + J) * 2048, pack_bf16(ay[b], ay[b + 1]), pack_bf16(ay[b + 4], ay[b + 5]),
                    pack_bf16(ay[b + 8], ay[b + 9]), pack_bf16(ay[b + 12], ay[b + 13]), r_full);
      }
    wg_wait<0>();
    fence_regs(ax);
    mbar_wait_cluster(bar_full, s & 1);
#pragma unroll
    for (int h = 0; h < 2; h++)
#pragma unroll
      for (int J = 0; J < 3; J++) {
        const int b = 16 * J + 2 * h;
        const uint4 r = lds128(xb + (h * 3 + J) * 2048);
        uint4 o;
        o.x = pack_bf16(ax[b] + bf_lo(r.x), ax[b + 1] + bf_hi(r.x));
        o.y = pack_bf16(ax[b + 4] + bf_lo(r.y), ax[b + 5] + bf_hi(r.y));
        o.z = pack_bf16(ax[b + 8] + bf_lo(r.z), ax[b + 9] + bf_hi(r.z));
        o.w = pack_bf16(ax[b + 12] + bf_lo(r.w), ax[b + 13] + bf_hi(r.w));
        *(uint4*)(optr + (size_t)s * 2 * 98304 + h * 8 * 192 + 64 * J) = o;
      }
    __syncwarp();
    if (lane == 0) mbar_arrive_remote(r_empty);
  }
  cluster_arrive();
  cluster_wait();
}

}

extern "C" void kernel_launch(void* const* d_in, const int* in_sizes, int n_in, void* d_out, int out_size) {
  (void)in_sizes;
  (void)n_in;
  (void)out_size;
  static bool attr_done = false;
  if (!attr_done) {
    cudaFuncSetAttribute(fpn_kernel, cudaFuncAttributeMaxDynamicSharedMemorySize, SMEM_BYTES);
    attr_done = true;
  }
  fpn_kernel<<<128, 256, SMEM_BYTES, cudaStreamPerThread>>>(
      (const __nv_bfloat16*)d_in[0], (const __nv_bfloat16*)d_in[1], (const __nv_bfloat16*)d_in[2],
      (const __nv_bfloat16*)d_in[3], (__nv_bfloat16*)d_out);
}
```

```cpp
#include <cuda_runtime.h>
#include <cuda_bf16.h>
#include <stdint.h>

namespace {

constexpr int IMG = 512;
constexpr int P = 67;
constexpr int PLANE = P * 16;
constexpr int TPOS = 6 * PLANE;
constexpr int T_BYTES = 4 * TPOS;
constexpr int UT = 9216;
constexpr int OFF_U = 0;
constexpr int OFF_WL = 12 * UT;
constexpr int OFF_T = OFF_WL + 9216;
constexpr int OFF_X = OFF_T + 2 * T_BYTES;
constexpr int X_BYTES = 12288;
constexpr int OFF_H = OFF_X + 2 * X_BYTES;
constexpr int HSIDE = 36 * 96;
constexpr int H_BYTES = 2 * HSIDE;
constexpr int OFF_BAR = OFF_H + 2 * H_BYTES;
constexpr int SMEM_BYTES = OFF_BAR + 64;
constexpr int NSTEP = 16;

#define R4(c, a, o) c(a[o]), c(a[o + 1]), c(a[o + 2]), c(a[o + 3])
#define R8(c, a, o) R4(c, a, o), R4(c, a, o + 4)
#define R24(c, a, o) R8(c, a, o), R8(c, a, o + 8), R8(c, a, o + 16)
#define RL24 \
  "%0, %1, %2, %3, %4, %5, %6, %7, %8, %9, %10, %11, %12, %13, %14, %15, %16, %17, %18, %19, %20, %21, %22, %23"
#define RL48                                                                                                       \
  RL24 ", %24, %25, %26, %27, %28, %29, %30, %31, %32, %33, %34, %35, %36, %37, %38, %39, %40, %41, %42, %43, %44, " \
       "%45, %46, %47"

template <bool INIT>
__device__ __forceinline__ void wgmma_ss_n96(float (&d)[48], uint64_t da, uint64_t db) {
  if constexpr (INIT) {
    asm volatile(
        "{\n.reg .pred p;\nsetp.ne.b32 p, 0, 0;\n"
        "wgmma.mma_async.sync.aligned.m64n96k16.f32.bf16.bf16 {" RL48 "}, %48, %49, p, 1, 1, 0, 0;\n}\n"
        : R24("=f", d, 0), R24("=f", d, 24)
        : "l"(da), "l"(db));
  } else {
    asm volatile(
        "{\n.reg .pred p;\nsetp.eq.b32 p, 0, 0;\n"
        "wgmma.mma_async.sync.aligned.m64n96k16.f32.bf16.bf16 {" RL48 "}, %48, %49, p, 1, 1, 0, 0;\n}\n"
        : R24("+f", d, 0), R24("+f", d, 24)
        : "l"(da), "l"(db));
  }
}
template <int O, bool INIT>
__device__ __forceinline__ void wgmma_rs_n48(float (&d)[48], uint32_t a0, uint32_t a1, uint32_t a2, uint32_t a3,
                                             uint64_t db) {
  if constexpr (INIT) {
    asm volatile(
        "{\n.reg .pred p;\nsetp.ne.b32 p, 0, 0;\n"
        "wgmma.mma_async.sync.aligned.m64n48k16.f32.bf16.bf16 {" RL24 "}, {%24, %25, %26, %27}, %28, p, 1, 1, 0;\n}\n"
        : R24("=f", d, O)
        : "r"(a0), "r"(a1), "r"(a2), "r"(a3), "l"(db));
  } else {
    asm volatile(
        "{\n.reg .pred p;\nsetp.eq.b32 p, 0, 0;\n"
        "wgmma.mma_async.sync.aligned.m64n48k16.f32.bf16.bf16 {" RL24 "}, {%24, %25, %26, %27}, %28, p, 1, 1, 0;\n}\n"
        : R24("+f", d, O)
        : "r"(a0), "r"(a1), "r"(a2), "r"(a3), "l"(db));
  }
}
__device__ __forceinline__ void wg_fence() { asm volatile("wgmma.fence.sync.aligned;" ::: "memory"); }
__device__ __forceinline__ void wg_commit() { asm volatile("wgmma.commit_group.sync.aligned;" ::: "memory"); }
template <int N>
__device__ __forceinline__ void wg_wait() {
  asm volatile("wgmma.wait_group.sync.aligned %0;" ::"n"(N) : "memory");
}
template <int N>
__device__ __forceinline__ void fence_regs(float (&a)[N]) {
#pragma unroll
  for (int i = 0; i < N; i++) asm volatile("" : "+f"(a[i])::"memory");
}
__device__ __forceinline__ uint64_t make_desc(uint32_t saddr, uint32_t lbo, uint32_t sbo) {
  return (uint64_t)((saddr & 0x3FFFF) >> 4) | ((uint64_t)(lbo >> 4) << 16) | ((uint64_t)(sbo >> 4) << 32);
}
__device__ __forceinline__ void fence_async_smem() { asm volatile("fence.proxy.async.shared::cta;" ::: "memory"); }
__device__ __forceinline__ void bar_wg(int id) { asm volatile("bar.sync %0, 128;" ::"r"(id) : "memory"); }

__device__ __forceinline__ uint32_t pack_bf16(float lo, float hi) {
  uint32_t r;
  asm("cvt.rn.bf16x2.f32 %0, %1, %2;" : "=r"(r) : "f"(hi), "f"(lo));
  return r;
}
__device__ __forceinline__ uint32_t hadd2(uint32_t a, uint32_t b) {
  uint32_t r;
  asm("add.rn.bf16x2 %0, %1, %2;" : "=r"(r) : "r"(a), "r"(b));
  return r;
}
__device__ __forceinline__ uint32_t hsub2(uint32_t a, uint32_t b) {
  uint32_t r;
  asm("sub.rn.bf16x2 %0, %1, %2;" : "=r"(r) : "r"(a), "r"(b));
  return r;
}
__device__ __forceinline__ uint32_t hfma2(uint32_t a, uint32_t b, uint32_t c) {
  uint32_t r;
  asm("fma.rn.bf16x2 %0, %1, %2, %3;" : "=r"(r) : "r"(a), "r"(b), "r"(c));
  return r;
}
__device__ __forceinline__ float bf_lo(uint32_t a) { return __uint_as_float(a << 16); }
__device__ __forceinline__ float bf_hi(uint32_t a) { return __uint_as_float(a & 0xffff0000u); }

__device__ __forceinline__ uint4 ldg128(const void* p) {
  uint4 v;
  asm volatile("ld.global.nc.L1::no_allocate.v4.u32 {%0,%1,%2,%3}, [%4];"
               : "=r"(v.x), "=r"(v.y), "=r"(v.z), "=r"(v.w)
               : "l"(p));
  return v;
}
__device__ __forceinline__ uint2 ldg64(const void* p) {
  uint2 v;
  asm volatile("ld.global.nc.L1::no_allocate.v2.u32 {%0,%1}, [%2];" : "=r"(v.x), "=r"(v.y) : "l"(p));
  return v;
}
__device__ __forceinline__ void sts64(uint32_t a, uint32_t x, uint32_t y) {
  asm volatile("st.shared.v2.u32 [%0], {%1,%2};" ::"r"(a), "r"(x), "r"(y) : "memory");
}
__device__ __forceinline__ void sts128(uint32_t a, uint32_t x, uint32_t y, uint32_t z, uint32_t w) {
  asm volatile("st.shared.v4.u32 [%0], {%1,%2,%3,%4};" ::"r"(a), "r"(x), "r"(y), "r"(z), "r"(w) : "memory");
}
__device__ __forceinline__ uint4 lds128(uint32_t a) {
  uint4 v;
  asm volatile("ld.shared.v4.u32 {%0,%1,%2,%3}, [%4];" : "=r"(v.x), "=r"(v.y), "=r"(v.z), "=r"(v.w) : "r"(a) : "memory");
  return v;
}
__device__ __forceinline__ void mbar_init(uint32_t bar, uint32_t cnt) {
  asm volatile("mbarrier.init.shared::cta.b64 [%0], %1;" ::"r"(bar), "r"(cnt) : "memory");
}
__device__ __forceinline__ void mbar_expect_tx(uint32_t bar, uint32_t bytes) {
  asm volatile("mbarrier.arrive.expect_tx.shared::cta.b64 _, [%0], %1;" ::"r"(bar), "r"(bytes) : "memory");
}
__device__ __forceinline__ void mbar_wait_cluster(uint32_t bar, uint32_t parity) {
  uint32_t ok;
  int it = 0;
  do {
    asm volatile(
        "{\n.reg .pred p;\n"
        "mbarrier.try_wait.parity.shared::cta.b64 p, [%1], %2;\n"
        "selp.u32 %0, 1, 0, p;\n}\n"
        : "=r"(ok)
        : "r"(bar), "r"(parity)
        : "memory");
    if (++it > (1 << 22)) __trap();
  } while (!ok);
}
__device__ __forceinline__ void mbar_arrive_remote(uint32_t rbar) {
  asm volatile("mbarrier.arrive.shared::cluster.b64 _, [%0];" ::"r"(rbar) : "memory");
}
__device__ __forceinline__ uint32_t mapa(uint32_t a, uint32_t rank) {
  uint32_t r;
  asm("mapa.shared::cluster.u32 %0, %1, %2;" : "=r"(r) : "r"(a), "r"(rank));
  return r;
}
__device__ __forceinline__ void st_async128(uint32_t ra, uint32_t x, uint32_t y, uint32_t z, uint32_t w, uint32_t rbar) {
  asm volatile("st.async.weak.shared::cluster.mbarrier::complete_tx::bytes.v4.b32 [%0], {%1,%2,%3,%4}, [%5];" ::"r"(ra),
               "r"(x), "r"(y), "r"(z), "r"(w), "r"(rbar)
               : "memory");
}
__device__ __forceinline__ void cluster_arrive() { asm volatile("barrier.cluster.arrive.release.aligned;" ::: "memory"); }
__device__ __forceinline__ void cluster_wait() { asm volatile("barrier.cluster.wait.acquire.aligned;" ::: "memory"); }

__device__ __forceinline__ uint32_t wsel(const uint4& v, int i) { return i == 0 ? v.x : i == 1 ? v.y : i == 2 ? v.z : v.w; }

struct CFrag {
  uint4 v[2][3];
};
struct AFrag {
  uint32_t a[6][4];
};
__device__ __forceinline__ uint32_t oxor(uint32_t a, uint32_t z) {
  uint32_t r;
  asm volatile("xor.b32 %0, %1, %2;" : "=r"(r) : "r"(a), "r"(z));
  return r;
}
__device__ __forceinline__ void make_frags(AFrag& f, const CFrag& c, uint32_t z) {
#pragma unroll
  for (int i = 0; i < 3; i++) {
    f.a[2 * i][0] = oxor(c.v[0][i].x, z);
    f.a[2 * i][1] = oxor(c.v[1][i].x, z);
    f.a[2 * i][2] = oxor(c.v[0][i].y, z);
    f.a[2 * i][3] = oxor(c.v[1][i].y, z);
    f.a[2 * i + 1][0] = oxor(c.v[0][i].z, z);
    f.a[2 * i + 1][1] = oxor(c.v[1][i].z, z);
    f.a[2 * i + 1][2] = oxor(c.v[0][i].w, z);
    f.a[2 * i + 1][3] = oxor(c.v[1][i].w, z);
  }
}
template <int O>
__device__ __forceinline__ void lateral_issue(float (&acc)[48], const AFrag& f, uint64_t dwl) {
#pragma unroll
  for (int k = 0; k < 6; k++) {
    if (k == 0)
      wgmma_rs_n48<O, true>(acc, f.a[k][0], f.a[k][1], f.a[k][2], f.a[k][3], dwl + (uint64_t)(k * 1536 >> 4));
    else
      wgmma_rs_n48<O, false>(acc, f.a[k][0], f.a[k][1], f.a[k][2], f.a[k][3], dwl + (uint64_t)(k * 1536 >> 4));
  }
}
template <int O>
__device__ __forceinline__ void lateral_finish(const float (&acc)[48], const uint2 (&p)[3], uint32_t (&d)[12]) {
#pragma unroll
  for (int h = 0; h < 2; h++)
#pragma unroll
    for (int jj = 0; jj < 3; jj++) {
      d[h * 6 + jj * 2 + 0] = hadd2(pack_bf16(acc[O + 4 * (2 * jj) + 2 * h], acc[O + 4 * (2 * jj) + 2 * h + 1]), p[jj].x);
      d[h * 6 + jj * 2 + 1] =
          hadd2(pack_bf16(acc[O + 4 * (2 * jj + 1) + 2 * h], acc[O + 4 * (2 * jj + 1) + 2 * h + 1]), p[jj].y);
    }
}

__global__ void __cluster_dims__(2, 1, 1) __launch_bounds__(256, 1)
    fpn_kernel(const __nv_bfloat16* __restrict__ c_fine, const __nv_bfloat16* __restrict__ p_coarse,
               const __nv_bfloat16* __restrict__ w_lat, const __nv_bfloat16* __restrict__ w_out,
               __nv_bfloat16* __restrict__ out, uint32_t zero) {
  extern __shared__ __align__(1024) unsigned char smem[];
  const uint32_t sb = (uint32_t)__cvta_generic_to_shared(smem);
  const int tid = threadIdx.x;
  const int wg = __shfl_sync(0xffffffffu, tid >> 7, 0);
  const int t128 = tid & 127;
  const int w = __shfl_sync(0xffffffffu, (tid >> 5) & 3, 0);
  const int lane = tid & 31;
  const int g = lane >> 2, q = lane & 3;
  uint32_t rank;
  asm("mov.u32 %0, %%cluster_ctarank;" : "=r"(rank));
  const int cl = blockIdx.x >> 1;
  const int y0 = (cl >> 2) * 32;
  const int x0 = ((cl & 3) * 2 + wg) * 64;

  const uint32_t bar_full = sb + OFF_BAR + wg * 16;
  const uint32_t bar_empty = bar_full + 8;
  if (tid == 0) {
    mbar_init(sb + OFF_BAR + 0, 1);
    mbar_init(sb + OFF_BAR + 8, 4);
    mbar_init(sb + OFF_BAR + 16, 1);
    mbar_init(sb + OFF_BAR + 24, 4);
    asm volatile("fence.mbarrier_init.release.cluster;" ::: "memory");
  }
  cluster_arrive();

  const unsigned char* cf = (const unsigned char*)c_fine;
  const unsigned char* pc = (const unsigned char*)p_coarse;

  CFrag ca, cb;
  uint2 pa[3], pb[3];
  const int hrow = 16 * w + 2 * g;
  {
    const int xl = max(x0 - 1, 0), xr = min(x0 + 64, IMG - 1);
#pragma unroll
    for (int h = 0; h < 2; h++) {
      const int yy = min(max(y0 - 2 + hrow + h, 0), IMG - 1);
#pragma unroll
      for (int i = 0; i < 3; i++) {
        ca.v[h][i] = ldg128(cf + ((size_t)yy * IMG + xl) * 192 + 64 * i + 16 * q);
        cb.v[h][i] = ldg128(cf + ((size_t)yy * IMG + xr) * 192 + 64 * i + 16 * q);
      }
    }
    const int py = min(max((y0 >> 1) - 1 + 8 * w + g, 0), 255);
#pragma unroll
    for (int jj = 0; jj < 3; jj++) {
      pa[jj] = ldg64(pc + ((size_t)py * 256 + (xl >> 1)) * 192 + 96 * rank + 32 * jj + 8 * q);
      pb[jj] = ldg64(pc + ((size_t)py * 256 + (xr >> 1)) * 192 + 96 * rank + 32 * jj + 8 * q);
    }
  }

  if (tid < 216) {
    const int dj = tid / 72, rem = tid % 72, kc = rem / 12, u = rem % 12;
    const unsigned char* src = (const unsigned char*)w_out + ((size_t)(dj * 96 + 48 * rank + 8 * kc) * 96 + 8 * u) * 2;
    uint4 v[3][8];
#pragma unroll
    for (int di = 0; di < 3; di++)
#pragma unroll
      for (int kk = 0; kk < 8; kk++) v[di][kk] = ldg128(src + (size_t)di * 3 * 96 * 192 + kk * 192);
    const uint32_t base = sb + OFF_U + dj * UT + kc * 1536 + (8 * (4 * (u >> 2)) + 2 * (u & 3)) * 16;
    const uint32_t o0 = rank ? 9 * UT : 0, o3 = rank ? 0 : 9 * UT;
    const float sg = rank ? -0.5f : 0.5f;
#pragma unroll
    for (int wd = 0; wd < 4; wd++) {
      uint32_t u0[2][4], u1[2][4], u2[2][4], u3[2][4];
#pragma unroll
      for (int kp = 0; kp < 4; kp++) {
        const uint32_t a0 = wsel(v[0][2 * kp], wd), a1 = wsel(v[0][2 * kp + 1], wd);
        const uint32_t b0 = wsel(v[1][2 * kp], wd), b1 = wsel(v[1][2 * kp + 1], wd);
        const uint32_t c0 = wsel(v[2][2 * kp], wd), c1 = wsel(v[2][2 * kp + 1], wd);
        u0[0][kp] = __byte_perm(a0, a1, 0x5410);
        u0[1][kp] = __byte_perm(a0, a1, 0x7632);
        u3[0][kp] = __byte_perm(c0, c1, 0x5410);
        u3[1][kp] = __byte_perm(c0, c1, 0x7632);
        const float s0l = bf_lo(a0) + bf_lo(c0), s1l = bf_lo(a1) + bf_lo(c1);
        const float s0h = bf_hi(a0) + bf_hi(c0), s1h = bf_hi(a1) + bf_hi(c1);
        u1[0][kp] = pack_bf16((s0l + bf_lo(b0)) * 0.5f, (s1l + bf_lo(b1)) * 0.5f);
        u1[1][kp] = pack_bf16((s0h + bf_hi(b0)) * 0.5f, (s1h + bf_hi(b1)) * 0.5f);
        u2[0][kp] = pack_bf16((s0l - bf_lo(b0)) * sg, (s1l - bf_lo(b1)) * sg);
        u2[1][kp] = pack_bf16((s0h - bf_hi(b0)) * sg, (s1h - bf_hi(b1)) * sg);
      }
#pragma unroll
      for (int e = 0; e < 2; e++) {
        const uint32_t a = base + (8 * wd + e) * 16;
        sts128(a + o0, u0[e][0], u0[e][1], u0[e][2], u0[e][3]);
        sts128(a + 3 * UT, u1[e][0], u1[e][1], u1[e][2], u1[e][3]);
        sts128(a + 6 * UT, u2[e][0], u2[e][1], u2[e][2], u2[e][3]);
        sts128(a + o3, u3[e][0], u3[e][1], u3[e][2], u3[e][3]);
      }
    }
  } else {
    for (int blk = tid - 216; blk < 72; blk += 40) {
      const int kc = blk / 6, u = blk % 6;
      const int i = kc >> 2, b = (kc >> 1) & 1, c = kc & 1;
      uint4 v[8];
#pragma unroll
      for (int kk = 0; kk < 8; kk++) {
        const int ch = 32 * i + 8 * (kk >> 1) + 4 * b + 2 * c + (kk & 1);
        v[kk] = ldg128((const unsigned char*)w_lat + ((size_t)ch * 96 + 48 * rank + 8 * u) * 2);
      }
      const int jj = u >> 1;
#pragma unroll
      for (int wd = 0; wd < 4; wd++) {
        const int qq = 2 * (u & 1) + (wd >> 1), jo = wd & 1;
        const uint32_t a = sb + OFF_WL + kc * 768 + (8 * (2 * jj + jo) + 2 * qq) * 16;
        uint32_t lo[4], hi[4];
#pragma unroll
        for (int kp = 0; kp < 4; kp++) {
          lo[kp] = __byte_perm(wsel(v[2 * kp], wd), wsel(v[2 * kp + 1], wd), 0x5410);
          hi[kp] = __byte_perm(wsel(v[2 * kp], wd), wsel(v[2 * kp + 1], wd), 0x7632);
        }
        sts128(a, lo[0], lo[1], lo[2], lo[3]);
        sts128(a + 16, hi[0], hi[1], hi[2], hi[3]);
      }
    }
  }
  fence_async_smem();
  __syncthreads();

  const uint64_t dwl = make_desc(sb + OFF_WL, 768, 128);
  const uint32_t tb = sb + OFF_T + wg * T_BYTES;
  const uint64_t dA = make_desc(tb, PLANE, 128);
  const uint64_t dB = make_desc(sb + OFF_U, 1536, 128);
  const uint32_t hb = sb + OFF_H + wg * H_BYTES;
  const uint32_t xb = sb + OFF_X + wg * X_BYTES + t128 * 16;
  const uint32_t peer = rank ^ 1;
  const uint32_t r_xb = mapa(xb, peer);
  const uint32_t r_full = mapa(bar_full, peer);
  const uint32_t r_empty = mapa(bar_empty, peer);

  const int pxl = 16 * w + 2 * g;
  const unsigned char* cptr = cf + ((size_t)x0 + pxl) * 192 + 16 * q;
  const unsigned char* pptr = pc + ((size_t)(x0 >> 1) + 8 * w + g) * 192 + 96 * rank + 8 * q;

  uint32_t d0[12], d1[12], d2[12], d3[12];
  float ax[48], ay[48];
  AFrag fa, fb;

  make_frags(fa, ca, zero);
  make_frags(fb, cb, zero);
  const int ra0 = max(y0 - 1, 0);
#pragma unroll
  for (int h = 0; h < 2; h++)
#pragma unroll
    for (int i = 0; i < 3; i++) {
      ca.v[h][i] = ldg128(cptr + (size_t)ra0 * 98304 + h * 192 + 64 * i);
      cb.v[h][i] = ldg128(cptr + (size_t)y0 * 98304 + h * 192 + 64 * i);
    }
  wg_fence();
  lateral_issue<0>(ax, fa, dwl);
  lateral_issue<24>(ax, fb, dwl);
  wg_commit();
  wg_wait<0>();
  fence_regs(ax);
  lateral_finish<0>(ax, pa, d0);
  lateral_finish<24>(ax, pb, d1);
#pragma unroll
  for (int jj = 0; jj < 3; jj++) {
    pa[jj] = ldg64(pptr + (size_t)(ra0 >> 1) * 49152 + 32 * jj);
    pb[jj] = ldg64(pptr + (size_t)(y0 >> 1) * 49152 + 32 * jj);
  }
  if (hrow < 36) {
#pragma unroll
    for (int h = 0; h < 2; h++) {
      const int yy = y0 - 2 + hrow + h;
      const bool rv = yy >= 0 && yy < IMG;
      const bool lv = rv && x0 > 0, rvv = rv && x0 + 64 < IMG;
#pragma unroll
      for (int jj = 0; jj < 3; jj++) {
        const uint32_t a = hb + (hrow + h) * 96 + 32 * jj + 8 * q;
        sts64(a, lv ? d0[h * 6 + jj * 2] : 0u, lv ? d0[h * 6 + jj * 2 + 1] : 0u);
        sts64(a + HSIDE, rvv ? d1[h * 6 + jj * 2] : 0u, rvv ? d1[h * 6 + jj * 2 + 1] : 0u);
      }
    }
  }

  make_frags(fa, ca, zero);
  make_frags(fb, cb, zero);
  cptr += (size_t)(y0 + 1) * 98304;
#pragma unroll
  for (int h = 0; h < 2; h++)
#pragma unroll
    for (int i = 0; i < 3; i++) {
      ca.v[h][i] = ldg128(cptr + h * 192 + 64 * i);
      cb.v[h][i] = ldg128(cptr + 98304 + h * 192 + 64 * i);
    }
  wg_fence();
  lateral_issue<0>(ax, fa, dwl);
  lateral_issue<24>(ax, fb, dwl);
  wg_commit();
  wg_wait<0>();
  fence_regs(ax);
  lateral_finish<0>(ax, pa, d0);
  lateral_finish<24>(ax, pb, d1);
  if (y0 == 0) {
#pragma unroll
    for (int i = 0; i < 12; i++) d0[i] = 0;
  }
  pptr += (size_t)((y0 >> 1) + 1) * 49152;
#pragma unroll
  for (int jj = 0; jj < 3; jj++) {
    pa[jj] = pb[jj];
    pb[jj] = ldg64(pptr + 32 * jj);
  }
  cluster_wait();

  const uint32_t ts = tb + (q >> 1) * PLANE + (pxl + 1) * 16 + (q & 1) * 8;
  const uint32_t ts0 = ts + (rank ? 3 * TPOS : 0);
  const uint32_t ts3 = ts + (rank ? 0 : 3 * TPOS);
  const int hside = lane >= 6 ? 1 : 0, hkc = lane - 6 * hside;
  uint32_t hsrcA = hb + hside * HSIDE + (1 + w) * 96 + hkc * 16;
  const uint32_t hoffB = ((w < 2 ? 2 : 1) - w) * 96;
  const uint32_t hsgn = (w == 1) ? 0x3f803f80u : 0xbf80bf80u;
  const int hslot = (w == 1 || w == 2) ? w : ((w == 0) != (rank != 0) ? 0 : 3);
  const uint32_t hdst = tb + hslot * TPOS + hkc * PLANE + (hside ? 65 * 16 : 0);

  unsigned char* optr = (unsigned char*)out + (((size_t)(y0 + rank) * IMG) + x0 + 16 * w + g) * 192 + 16 * q;
  const bool last_block = (y0 + 32 == IMG);

#pragma unroll 1
  for (int s = 0; s < NSTEP; s++) {
    make_frags(fa, ca, zero);
    make_frags(fb, cb, zero);
    {
      const bool lastb = last_block && s == NSTEP - 2;
      if (s + 1 < NSTEP) cptr += 2 * 98304;
      const unsigned char* cptr2 = cptr + ((lastb || (last_block && s == NSTEP - 1)) ? 0 : 98304);
#pragma unroll
      for (int h = 0; h < 2; h++)
#pragma unroll
        for (int i = 0; i < 3; i++) {
          ca.v[h][i] = ldg128(cptr + h * 192 + 64 * i);
          cb.v[h][i] = ldg128(cptr2 + h * 192 + 64 * i);
        }
      if (s + 1 < NSTEP && !lastb) pptr += 49152;
    }
    wg_fence();
    lateral_issue<0>(ax, fa, dwl);
    lateral_issue<24>(ax, fb, dwl);
    wg_commit();
    wg_wait<0>();
    fence_regs(ax);
    if (t128 == 0) mbar_expect_tx(bar_full, X_BYTES);
    lateral_finish<0>(ax, pa, d2);
    lateral_finish<24>(ax, pb, d3);
    if (last_block && s == NSTEP - 1) {
#pragma unroll
      for (int i = 0; i < 12; i++) d3[i] = 0;
    }
#pragma unroll
    for (int jj = 0; jj < 3; jj++) {
      pa[jj] = pb[jj];
      pb[jj] = ldg64(pptr + 32 * jj);
    }
    bar_wg(1 + wg);
#pragma unroll
    for (int h = 0; h < 2; h++)
#pragma unroll
      for (int jj = 0; jj < 3; jj++) {
        const int i0 = h * 6 + jj * 2;
        const uint32_t o = 2 * jj * PLANE + h * 16;
        sts64(ts + TPOS + o, hadd2(d1[i0], d2[i0]), hadd2(d1[i0 + 1], d2[i0 + 1]));
        sts64(ts + 2 * TPOS + o, hsub2(d2[i0], d1[i0]), hsub2(d2[i0 + 1], d1[i0 + 1]));
        sts64(ts0 + o, hsub2(d0[i0], d2[i0]), hsub2(d0[i0 + 1], d2[i0 + 1]));
        sts64(ts3 + o, hsub2(d3[i0], d1[i0]), hsub2(d3[i0 + 1], d1[i0 + 1]));
      }
    if (lane < 12) {
      const uint4 a = lds128(hsrcA), b = lds128(hsrcA + hoffB);
      sts128(hdst, hfma2(b.x, hsgn, a.x), hfma2(b.y, hsgn, a.y), hfma2(b.z, hsgn, a.z), hfma2(b.w, hsgn, a.w));
    }
    hsrcA += 192;
#pragma unroll
    for (int i = 0; i < 12; i++) {
      d0[i] = d2[i];
      d1[i] = d3[i];
    }
    fence_async_smem();
    bar_wg(1 + wg);

    wg_fence();
#pragma unroll
    for (int dj = 0; dj < 3; dj++)
#pragma unroll
      for (int ks = 0; ks < 3; ks++) {
        const uint64_t a1 = dA + (uint64_t)((1 * TPOS + 2 * ks * PLANE + dj * 16) >> 4);
        const uint64_t b1 = dB + (uint64_t)(((3 + dj) * UT + 2 * ks * 1536) >> 4);
        const uint64_t a2 = dA + (uint64_t)((2 * TPOS + 2 * ks * PLANE + dj * 16) >> 4);
        const uint64_t b2 = dB + (uint64_t)(((6 + dj) * UT + 2 * ks * 1536) >> 4);
        if (dj == 0 && ks == 0) {
          wgmma_ss_n96<true>(ax, a1, b1);
          wgmma_ss_n96<true>(ay, a2, b2);
        } else {
          wgmma_ss_n96<false>(ax, a1, b1);
          wgmma_ss_n96<false>(ay, a2, b2);
        }
      }
    wg_commit();
    wg_wait<0>();
    fence_regs(ax);
    fence_regs(ay);
    mbar_wait_cluster(bar_empty, (s & 1) ^ 1);
#pragma unroll
    for (int i = 0; i < 48; i++) {
      const float a = ax[i], b = ay[i];
      ax[i] = a + b;
      ay[i] = a - b;
    }
    fence_regs(ax);
    fence_regs(ay);
    wg_fence();
#pragma unroll
    for (int dj = 0; dj < 3; dj++)
#pragma unroll
      for (int ks = 0; ks < 3; ks++)
        wgmma_ss_n96<false>(ay, dA + (uint64_t)((3 * TPOS + 2 * ks * PLANE + dj * 16) >> 4),
                            dB + (uint64_t)(((9 + dj) * UT + 2 * ks * 1536) >> 4));
    wg_commit();
#pragma unroll
    for (int dj = 0; dj < 3; dj++)
#pragma unroll
      for (int ks = 0; ks < 3; ks++)
        wgmma_ss_n96<false>(ax, dA + (uint64_t)((0 * TPOS + 2 * ks * PLANE + dj * 16) >> 4),
                            dB + (uint64_t)(((0 + dj) * UT + 2 * ks * 1536) >> 4));
    wg_commit();
    wg_wait<1>();
    fence_regs(ay);
#pragma unroll
    for (int h = 0; h < 2; h++)
#pragma unroll
      for (int J = 0; J < 3; J++) {
        const int b = 16 * J + 2 * h;
        st_async128(r_xb + (h * 3 + J) * 2048, pack_bf16(ay[b], ay[b + 1]), pack_bf16(ay[b + 4], ay[b + 5]),
                    pack_bf16(ay[b + 8], ay[b + 9]), pack_bf16(ay[b + 12], ay[b + 13]), r_full);
      }
    wg_wait<0>();
    fence_regs(ax);
    mbar_wait_cluster(bar_full, s & 1);
#pragma unroll
    for (int h = 0; h < 2; h++)
#pragma unroll
      for (int J = 0; J < 3; J++) {
        const int b = 16 * J + 2 * h;
        const uint4 r = lds128(xb + (h * 3 + J) * 2048);
        uint4 o;
        o.x = pack_bf16(ax[b] + bf_lo(r.x), ax[b + 1] + bf_hi(r.x));
        o.y = pack_bf16(ax[b + 4] + bf_lo(r.y), ax[b + 5] + bf_hi(r.y));
        o.z = pack_bf16(ax[b + 8] + bf_lo(r.z), ax[b + 9] + bf_hi(r.z));
        o.w = pack_bf16(ax[b + 12] + bf_lo(r.w), ax[b + 13] + bf_hi(r.w));
        *(uint4*)(optr + h * 8 * 192 + 64 * J) = o;
      }
    optr += 2 * 98304;
    __syncwarp();
    if (lane == 0) mbar_arrive_remote(r_empty);
  }
  cluster_arrive();
  cluster_wait();
}

}

extern "C" void kernel_launch(void* const* d_in, const int* in_sizes, int n_in, void* d_out, int out_size) {
  (void)in_sizes;
  (void)n_in;
  (void)out_size;
  static bool attr_done = false;
  if (!attr_done) {
    cudaFuncSetAttribute(fpn_kernel, cudaFuncAttributeMaxDynamicSharedMemorySize, SMEM_BYTES);
    attr_done = true;
  }
  fpn_kernel<<<128, 256, SMEM_BYTES, cudaStreamPerThread>>>(
      (const __nv_bfloat16*)d_in[0], (const __nv_bfloat16*)d_in[1], (const __nv_bfloat16*)d_in[2],
      (const __nv_bfloat16*)d_in[3], (__nv_bfloat16*)d_out, 0u);
}
```

```cpp
#include <cuda_runtime.h>
#include <cuda_bf16.h>
#include <stdint.h>

namespace {

constexpr int IMG = 512;
constexpr int P = 67;
constexpr int PLANE = P * 16;
constexpr int TPOS = 6 * PLANE;
constexpr int T_BYTES = 4 * TPOS;
constexpr int UT = 9216;
constexpr int OFF_U = 0;
constexpr int OFF_WL = 12 * UT;
constexpr int OFF_T = OFF_WL + 9216;
constexpr int OFF_X = OFF_T + 2 * T_BYTES;
constexpr int X_BYTES = 12288;
constexpr int OFF_H = OFF_X + 2 * X_BYTES;
constexpr int HSIDE = 36 * 96;
constexpr int H_BYTES = 2 * HSIDE;
constexpr int OFF_BAR = OFF_H + 2 * H_BYTES;
constexpr int SMEM_BYTES = OFF_BAR + 64;
constexpr int NSTEP = 16;

#define R4(c, a, o) c(a[o]), c(a[o + 1]), c(a[o + 2]), c(a[o + 3])
#define R8(c, a, o) R4(c, a, o), R4(c, a, o + 4)
#define R24(c, a, o) R8(c, a, o), R8(c, a, o + 8), R8(c, a, o + 16)
#define RL24 \
  "%0, %1, %2, %3, %4, %5, %6, %7, %8, %9, %10, %11, %12, %13, %14, %15, %16, %17, %18, %19, %20, %21, %22, %23"
#define RL48                                                                                                       \
  RL24 ", %24, %25, %26, %27, %28, %29, %30, %31, %32, %33, %34, %35, %36, %37, %38, %39, %40, %41, %42, %43, %44, " \
       "%45, %46, %47"

template <bool INIT>
__device__ __forceinline__ void wgmma_ss_n96(float (&d)[48], uint64_t da, uint64_t db) {
  if constexpr (INIT) {
    asm volatile(
        "{\n.reg .pred p;\nsetp.ne.b32 p, 0, 0;\n"
        "wgmma.mma_async.sync.aligned.m64n96k16.f32.bf16.bf16 {" RL48 "}, %48, %49, p, 1, 1, 0, 0;\n}\n"
        : R24("=f", d, 0), R24("=f", d, 24)
        : "l"(da), "l"(db));
  } else {
    asm volatile(
        "{\n.reg .pred p;\nsetp.eq.b32 p, 0, 0;\n"
        "wgmma.mma_async.sync.aligned.m64n96k16.f32.bf16.bf16 {" RL48 "}, %48, %49, p, 1, 1, 0, 0;\n}\n"
        : R24("+f", d, 0), R24("+f", d, 24)
        : "l"(da), "l"(db));
  }
}
template <int O, bool INIT>
__device__ __forceinline__ void wgmma_rs_n48(float (&d)[48], uint32_t a0, uint32_t a1, uint32_t a2, uint32_t a3,
                                             uint64_t db) {
  if constexpr (INIT) {
    asm volatile(
        "{\n.reg .pred p;\nsetp.ne.b32 p, 0, 0;\n"
        "wgmma.mma_async.sync.aligned.m64n48k16.f32.bf16.bf16 {" RL24 "}, {%24, %25, %26, %27}, %28, p, 1, 1, 0;\n}\n"
        : R24("=f", d, O)
        : "r"(a0), "r"(a1), "r"(a2), "r"(a3), "l"(db));
  } else {
    asm volatile(
        "{\n.reg .pred p;\nsetp.eq.b32 p, 0, 0;\n"
        "wgmma.mma_async.sync.aligned.m64n48k16.f32.bf16.bf16 {" RL24 "}, {%24, %25, %26, %27}, %28, p, 1, 1, 0;\n}\n"
        : R24("+f", d, O)
        : "r"(a0), "r"(a1), "r"(a2), "r"(a3), "l"(db));
  }
}
__device__ __forceinline__ void wg_fence() { asm volatile("wgmma.fence.sync.aligned;" ::: "memory"); }
__device__ __forceinline__ void wg_commit() { asm volatile("wgmma.commit_group.sync.aligned;" ::: "memory"); }
template <int N>
__device__ __forceinline__ void wg_wait() {
  asm volatile("wgmma.wait_group.sync.aligned %0;" ::"n"(N) : "memory");
}
template <int N>
__device__ __forceinline__ void fence_regs(float (&a)[N]) {
#pragma unroll
  for (int i = 0; i < N; i++) asm volatile("" : "+f"(a[i])::"memory");
}
__device__ __forceinline__ uint64_t make_desc(uint32_t saddr, uint32_t lbo, uint32_t sbo) {
  return (uint64_t)((saddr & 0x3FFFF) >> 4) | ((uint64_t)(lbo >> 4) << 16) | ((uint64_t)(sbo >> 4) << 32);
}
__device__ __forceinline__ void fence_async_smem() { asm volatile("fence.proxy.async.shared::cta;" ::: "memory"); }
__device__ __forceinline__ void bar_wg(int id) { asm volatile("bar.sync %0, 128;" ::"r"(id) : "memory"); }

__device__ __forceinline__ uint32_t pack_bf16(float lo, float hi) {
  uint32_t r;
  asm("cvt.rn.bf16x2.f32 %0, %1, %2;" : "=r"(r) : "f"(hi), "f"(lo));
  return r;
}
__device__ __forceinline__ uint32_t hadd2(uint32_t a, uint32_t b) {
  uint32_t r;
  asm("add.rn.bf16x2 %0, %1, %2;" : "=r"(r) : "r"(a), "r"(b));
  return r;
}
__device__ __forceinline__ uint32_t hsub2(uint32_t a, uint32_t b) {
  uint32_t r;
  asm("sub.rn.bf16x2 %0, %1, %2;" : "=r"(r) : "r"(a), "r"(b));
  return r;
}
__device__ __forceinline__ uint32_t hfma2(uint32_t a, uint32_t b, uint32_t c) {
  uint32_t r;
  asm("fma.rn.bf16x2 %0, %1, %2, %3;" : "=r"(r) : "r"(a), "r"(b), "r"(c));
  return r;
}
__device__ __forceinline__ float bf_lo(uint32_t a) { return __uint_as_float(a << 16); }
__device__ __forceinline__ float bf_hi(uint32_t a) { return __uint_as_float(a & 0xffff0000u); }

__device__ __forceinline__ uint4 ldg128(const void* p) {
  uint4 v;
  asm volatile("ld.global.nc.L1::no_allocate.v4.u32 {%0,%1,%2,%3}, [%4];"
               : "=r"(v.x), "=r"(v.y), "=r"(v.z), "=r"(v.w)
               : "l"(p));
  return v;
}
__device__ __forceinline__ uint2 ldg64(const void* p) {
  uint2 v;
  asm volatile("ld.global.nc.L1::no_allocate.v2.u32 {%0,%1}, [%2];" : "=r"(v.x), "=r"(v.y) : "l"(p));
  return v;
}
__device__ __forceinline__ void sts64(uint32_t a, uint32_t x, uint32_t y) {
  asm volatile("st.shared.v2.u32 [%0], {%1,%2};" ::"r"(a), "r"(x), "r"(y) : "memory");
}
__device__ __forceinline__ void sts128(uint32_t a, uint32_t x, uint32_t y, uint32_t z, uint32_t w) {
  asm volatile("st.shared.v4.u32 [%0], {%1,%2,%3,%4};" ::"r"(a), "r"(x), "r"(y), "r"(z), "r"(w) : "memory");
}
__device__ __forceinline__ uint4 lds128(uint32_t a) {
  uint4 v;
  asm volatile("ld.shared.v4.u32 {%0,%1,%2,%3}, [%4];" : "=r"(v.x), "=r"(v.y), "=r"(v.z), "=r"(v.w) : "r"(a) : "memory");
  return v;
}
__device__ __forceinline__ void mbar_init(uint32_t bar, uint32_t cnt) {
  asm volatile("mbarrier.init.shared::cta.b64 [%0], %1;" ::"r"(bar), "r"(cnt) : "memory");
}
__device__ __forceinline__ void mbar_expect_tx(uint32_t bar, uint32_t bytes) {
  asm volatile("mbarrier.arrive.expect_tx.shared::cta.b64 _, [%0], %1;" ::"r"(bar), "r"(bytes) : "memory");
}
__device__ __forceinline__ void mbar_wait_cluster(uint32_t bar, uint32_t parity) {
  uint32_t ok;
  int it = 0;
  do {
    asm volatile(
        "{\n.reg .pred p;\n"
        "mbarrier.try_wait.parity.shared::cta.b64 p, [%1], %2;\n"
        "selp.u32 %0, 1, 0, p;\n}\n"
        : "=r"(ok)
        : "r"(bar), "r"(parity)
        : "memory");
    if (++it > (1 << 22)) __trap();
  } while (!ok);
}
__device__ __forceinline__ void mbar_arrive_remote(uint32_t rbar) {
  asm volatile("mbarrier.arrive.shared::cluster.b64 _, [%0];" ::"r"(rbar) : "memory");
}
__device__ __forceinline__ uint32_t mapa(uint32_t a, uint32_t rank) {
  uint32_t r;
  asm("mapa.shared::cluster.u32 %0, %1, %2;" : "=r"(r) : "r"(a), "r"(rank));
  return r;
}
__device__ __forceinline__ void st_async128(uint32_t ra, uint32_t x, uint32_t y, uint32_t z, uint32_t w, uint32_t rbar) {
  asm volatile("st.async.weak.shared::cluster.mbarrier::complete_tx::bytes.v4.b32 [%0], {%1,%2,%3,%4}, [%5];" ::"r"(ra),
               "r"(x), "r"(y), "r"(z), "r"(w), "r"(rbar)
               : "memory");
}
__device__ __forceinline__ void bulk_copy_cluster_pred(uint32_t rdst, uint32_t src, uint32_t bytes, uint32_t rbar,
                                                       uint32_t pred) {
  asm volatile(
      "{\n.reg .pred p;\nsetp.ne.b32 p, %4, 0;\n"
      "@p cp.async.bulk.shared::cluster.shared::cta.mbarrier::complete_tx::bytes [%0], [%1], %2, [%3];\n}\n" ::"r"(rdst),
      "r"(src), "r"(bytes), "r"(rbar), "r"(pred)
      : "memory");
}
__device__ __forceinline__ void cluster_arrive() { asm volatile("barrier.cluster.arrive.release.aligned;" ::: "memory"); }
__device__ __forceinline__ void cluster_wait() { asm volatile("barrier.cluster.wait.acquire.aligned;" ::: "memory"); }

__device__ __forceinline__ uint32_t wsel(const uint4& v, int i) { return i == 0 ? v.x : i == 1 ? v.y : i == 2 ? v.z : v.w; }

struct CFrag {
  uint4 v[2][3];
};
struct AFrag {
  uint32_t a[6][4];
};
__device__ __forceinline__ uint32_t oxor(uint32_t a, uint32_t z) {
  uint32_t r;
  asm volatile("xor.b32 %0, %1, %2;" : "=r"(r) : "r"(a), "r"(z));
  return r;
}
__device__ __forceinline__ void make_frags(AFrag& f, const CFrag& c, uint32_t z) {
#pragma unroll
  for (int i = 0; i < 3; i++) {
    f.a[2 * i][0] = oxor(c.v[0][i].x, z);
    f.a[2 * i][1] = oxor(c.v[1][i].x, z);
    f.a[2 * i][2] = oxor(c.v[0][i].y, z);
    f.a[2 * i][3] = oxor(c.v[1][i].y, z);
    f.a[2 * i + 1][0] = oxor(c.v[0][i].z, z);
    f.a[2 * i + 1][1] = oxor(c.v[1][i].z, z);
    f.a[2 * i + 1][2] = oxor(c.v[0][i].w, z);
    f.a[2 * i + 1][3] = oxor(c.v[1][i].w, z);
  }
}
template <int O>
__device__ __forceinline__ void lateral_issue(float (&acc)[48], const AFrag& f, uint64_t dwl) {
#pragma unroll
  for (int k = 0; k < 6; k++) {
    if (k == 0)
      wgmma_rs_n48<O, true>(acc, f.a[k][0], f.a[k][1], f.a[k][2], f.a[k][3], dwl + (uint64_t)(k * 1536 >> 4));
    else
      wgmma_rs_n48<O, false>(acc, f.a[k][0], f.a[k][1], f.a[k][2], f.a[k][3], dwl + (uint64_t)(k * 1536 >> 4));
  }
}
template <int O>
__device__ __forceinline__ void lateral_finish(const float (&acc)[48], const uint2 (&p)[3], uint32_t (&d)[12]) {
#pragma unroll
  for (int h = 0; h < 2; h++)
#pragma unroll
    for (int jj = 0; jj < 3; jj++) {
      d[h * 6 + jj * 2 + 0] = hadd2(pack_bf16(acc[O + 4 * (2 * jj) + 2 * h], acc[O + 4 * (2 * jj) + 2 * h + 1]), p[jj].x);
      d[h * 6 + jj * 2 + 1] =
          hadd2(pack_bf16(acc[O + 4 * (2 * jj + 1) + 2 * h], acc[O + 4 * (2 * jj + 1) + 2 * h + 1]), p[jj].y);
    }
}

__global__ void __cluster_dims__(2, 1, 1) __launch_bounds__(256, 1)
    fpn_kernel(const __nv_bfloat16* __restrict__ c_fine, const __nv_bfloat16* __restrict__ p_coarse,
               const __nv_bfloat16* __restrict__ w_lat, const __nv_bfloat16* __restrict__ w_out,
               __nv_bfloat16* __restrict__ out, uint32_t zero) {
  extern __shared__ __align__(1024) unsigned char smem[];
  const uint32_t sb = (uint32_t)__cvta_generic_to_shared(smem);
  const int tid = threadIdx.x;
  const int wg = __shfl_sync(0xffffffffu, tid >> 7, 0);
  const int t128 = tid & 127;
  const int w = __shfl_sync(0xffffffffu, (tid >> 5) & 3, 0);
  const int lane = tid & 31;
  const int g = lane >> 2, q = lane & 3;
  uint32_t rank;
  asm("mov.u32 %0, %%cluster_ctarank;" : "=r"(rank));
  const int cl = blockIdx.x >> 1;
  const int y0 = (cl >> 2) * 32;
  const int x0 = ((cl & 3) * 2 + wg) * 64;

  const uint32_t bar_full = sb + OFF_BAR + wg * 16;
  const uint32_t bar_empty = bar_full + 8;
  if (tid == 0) {
    mbar_init(sb + OFF_BAR + 0, 1);
    mbar_init(sb + OFF_BAR + 8, 4);
    mbar_init(sb + OFF_BAR + 16, 1);
    mbar_init(sb + OFF_BAR + 24, 4);
    asm volatile("fence.mbarrier_init.release.cluster;" ::: "memory");
  }
  cluster_arrive();

  const unsigned char* cf = (const unsigned char*)c_fine;
  const unsigned char* pc = (const unsigned char*)p_coarse;

  CFrag ca, cb;
  uint2 pa[3], pb[3];
  const int hrow = 16 * w + 2 * g;
  {
    const int xl = max(x0 - 1, 0), xr = min(x0 + 64, IMG - 1);
#pragma unroll
    for (int h = 0; h < 2; h++) {
      const int yy = min(max(y0 - 2 + hrow + h, 0), IMG - 1);
#pragma unroll
      for (int i = 0; i < 3; i++) {
        ca.v[h][i] = ldg128(cf + ((size_t)yy * IMG + xl) * 192 + 64 * i + 16 * q);
        cb.v[h][i] = ldg128(cf + ((size_t)yy * IMG + xr) * 192 + 64 * i + 16 * q);
      }
    }
    const int py = min(max((y0 >> 1) - 1 + 8 * w + g, 0), 255);
#pragma unroll
    for (int jj = 0; jj < 3; jj++) {
      pa[jj] = ldg64(pc + ((size_t)py * 256 + (xl >> 1)) * 192 + 96 * rank + 32 * jj + 8 * q);
      pb[jj] = ldg64(pc + ((size_t)py * 256 + (xr >> 1)) * 192 + 96 * rank + 32 * jj + 8 * q);
    }
  }

  if (tid < 216) {
    const int dj = tid / 72, rem = tid % 72, kc = rem / 12, u = rem % 12;
    const unsigned char* src = (const unsigned char*)w_out + ((size_t)(dj * 96 + 48 * rank + 8 * kc) * 96 + 8 * u) * 2;
    uint4 v[3][8];
#pragma unroll
    for (int di = 0; di < 3; di++)
#pragma unroll
      for (int kk = 0; kk < 8; kk++) v[di][kk] = ldg128(src + (size_t)di * 3 * 96 * 192 + kk * 192);
    const uint32_t base = sb + OFF_U + dj * UT + kc * 1536 + (8 * (4 * (u >> 2)) + 2 * (u & 3)) * 16;
    const uint32_t o0 = rank ? 9 * UT : 0, o3 = rank ? 0 : 9 * UT;
    const float sg = rank ? -0.5f : 0.5f;
#pragma unroll
    for (int wd = 0; wd < 4; wd++) {
      uint32_t u0[2][4], u1[2][4], u2[2][4], u3[2][4];
#pragma unroll
      for (int kp = 0; kp < 4; kp++) {
        const uint32_t a0 = wsel(v[0][2 * kp], wd), a1 = wsel(v[0][2 * kp + 1], wd);
        const uint32_t b0 = wsel(v[1][2 * kp], wd), b1 = wsel(v[1][2 * kp + 1], wd);
        const uint32_t c0 = wsel(v[2][2 * kp], wd), c1 = wsel(v[2][2 * kp + 1], wd);
        u0[0][kp] = __byte_perm(a0, a1, 0x5410);
        u0[1][kp] = __byte_perm(a0, a1, 0x7632);
        u3[0][kp] = __byte_perm(c0, c1, 0x5410);
        u3[1][kp] = __byte_perm(c0, c1, 0x7632);
        const float s0l = bf_lo(a0) + bf_lo(c0), s1l = bf_lo(a1) + bf_lo(c1);
        const float s0h = bf_hi(a0) + bf_hi(c0), s1h = bf_hi(a1) + bf_hi(c1);
        u1[0][kp] = pack_bf16((s0l + bf_lo(b0)) * 0.5f, (s1l + bf_lo(b1)) * 0.5f);
        u1[1][kp] = pack_bf16((s0h + bf_hi(b0)) * 0.5f, (s1h + bf_hi(b1)) * 0.5f);
        u2[0][kp] = pack_bf16((s0l - bf_lo(b0)) * sg, (s1l - bf_lo(b1)) * sg);
        u2[1][kp] = pack_bf16((s0h - bf_hi(b0)) * sg, (s1h - bf_hi(b1)) * sg);
      }
#pragma unroll
      for (int e = 0; e < 2; e++) {
        const uint32_t a = base + (8 * wd + e) * 16;
        sts128(a + o0, u0[e][0], u0[e][1], u0[e][2], u0[e][3]);
        sts128(a + 3 * UT, u1[e][0], u1[e][1], u1[e][2], u1[e][3]);
        sts128(a + 6 * UT, u2[e][0], u2[e][1], u2[e][2], u2[e][3]);
        sts128(a + o3, u3[e][0], u3[e][1], u3[e][2], u3[e][3]);
      }
    }
  } else {
    for (int blk = tid - 216; blk < 72; blk += 40) {
      const int kc = blk / 6, u = blk % 6;
      const int i = kc >> 2, b = (kc >> 1) & 1, c = kc & 1;
      uint4 v[8];
#pragma unroll
      for (int kk = 0; kk < 8; kk++) {
        const int ch = 32 * i + 8 * (kk >> 1) + 4 * b + 2 * c + (kk & 1);
        v[kk] = ldg128((const unsigned char*)w_lat + ((size_t)ch * 96 + 48 * rank + 8 * u) * 2);
      }
      const int jj = u >> 1;
#pragma unroll
      for (int wd = 0; wd < 4; wd++) {
        const int qq = 2 * (u & 1) + (wd >> 1), jo = wd & 1;
        const uint32_t a = sb + OFF_WL + kc * 768 + (8 * (2 * jj + jo) + 2 * qq) * 16;
        uint32_t lo[4], hi[4];
#pragma unroll
        for (int kp = 0; kp < 4; kp++) {
          lo[kp] = __byte_perm(wsel(v[2 * kp], wd), wsel(v[2 * kp + 1], wd), 0x5410);
          hi[kp] = __byte_perm(wsel(v[2 * kp], wd), wsel(v[2 * kp + 1], wd), 0x7632);
        }
        sts128(a, lo[0], lo[1], lo[2], lo[3]);
        sts128(a + 16, hi[0], hi[1], hi[2], hi[3]);
      }
    }
  }
  fence_async_smem();
  __syncthreads();

  const uint64_t dwl = make_desc(sb + OFF_WL, 768, 128);
  const uint32_t tb = sb + OFF_T + wg * T_BYTES;
  const uint64_t dA = make_desc(tb, PLANE, 128);
  const uint64_t dB = make_desc(sb + OFF_U, 1536, 128);
  const uint32_t hb = sb + OFF_H + wg * H_BYTES;
  const uint32_t xw = sb + OFF_X + wg * X_BYTES + w * 3072;
  const uint32_t xb = xw + lane * 16;
  const uint32_t sw = tb + TPOS + w * 3072;
  const uint32_t peer = rank ^ 1;
  const uint32_t r_xw = mapa(xw, peer);
  const uint32_t r_full = mapa(bar_full, peer);
  const uint32_t r_empty = mapa(bar_empty, peer);

  const int pxl = 16 * w + 2 * g;
  const unsigned char* cptr = cf + ((size_t)x0 + pxl) * 192 + 16 * q;
  const unsigned char* pptr = pc + ((size_t)(x0 >> 1) + 8 * w + g) * 192 + 96 * rank + 8 * q;

  uint32_t d0[12], d1[12], d2[12], d3[12];
  float ax[48], ay[48];
  AFrag fa, fb;

  make_frags(fa, ca, zero);
  make_frags(fb, cb, zero);
  const int ra0 = max(y0 - 1, 0);
#pragma unroll
  for (int h = 0; h < 2; h++)
#pragma unroll
    for (int i = 0; i < 3; i++) {
      ca.v[h][i] = ldg128(cptr + (size_t)ra0 * 98304 + h * 192 + 64 * i);
      cb.v[h][i] = ldg128(cptr + (size_t)y0 * 98304 + h * 192 + 64 * i);
    }
  wg_fence();
  lateral_issue<0>(ax, fa, dwl);
  lateral_issue<24>(ax, fb, dwl);
  wg_commit();
  wg_wait<0>();
  fence_regs(ax);
  lateral_finish<0>(ax, pa, d0);
  lateral_finish<24>(ax, pb, d1);
#pragma unroll
  for (int jj = 0; jj < 3; jj++) {
    pa[jj] = ldg64(pptr + (size_t)(ra0 >> 1) * 49152 + 32 * jj);
    pb[jj] = ldg64(pptr + (size_t)(y0 >> 1) * 49152 + 32 * jj);
  }
  if (hrow < 36) {
#pragma unroll
    for (int h = 0; h < 2; h++) {
      const int yy = y0 - 2 + hrow + h;
      const bool rv = yy >= 0 && yy < IMG;
      const bool lv = rv && x0 > 0, rvv = rv && x0 + 64 < IMG;
#pragma unroll
      for (int jj = 0; jj < 3; jj++) {
        const uint32_t a = hb + (hrow + h) * 96 + 32 * jj + 8 * q;
        sts64(a, lv ? d0[h * 6 + jj * 2] : 0u, lv ? d0[h * 6 + jj * 2 + 1] : 0u);
        sts64(a + HSIDE, rvv ? d1[h * 6 + jj * 2] : 0u, rvv ? d1[h * 6 + jj * 2 + 1] : 0u);
      }
    }
  }

  make_frags(fa, ca, zero);
  make_frags(fb, cb, zero);
  cptr += (size_t)(y0 + 1) * 98304;
#pragma unroll
  for (int h = 0; h < 2; h++)
#pragma unroll
    for (int i = 0; i < 3; i++) {
      ca.v[h][i] = ldg128(cptr + h * 192 + 64 * i);
      cb.v[h][i] = ldg128(cptr + 98304 + h * 192 + 64 * i);
    }
  wg_fence();
  lateral_issue<0>(ax, fa, dwl);
  lateral_issue<24>(ax, fb, dwl);
  wg_commit();
  wg_wait<0>();
  fence_regs(ax);
  lateral_finish<0>(ax, pa, d0);
  lateral_finish<24>(ax, pb, d1);
  if (y0 == 0) {
#pragma unroll
    for (int i = 0; i < 12; i++) d0[i] = 0;
  }
  pptr += (size_t)(y0 >> 1) * 49152;
#pragma unroll
  for (int jj = 0; jj < 3; jj++) {
    pa[jj] = ldg64(pptr + 32 * jj);
    pb[jj] = ldg64(pptr + 49152 + 32 * jj);
  }
  cluster_wait();

  const uint32_t ts = tb + (q >> 1) * PLANE + (pxl + 1) * 16 + (q & 1) * 8;
  const uint32_t ts0 = ts + (rank ? 3 * TPOS : 0);
  const uint32_t ts3 = ts + (rank ? 0 : 3 * TPOS);
  const int hside = lane >= 6 ? 1 : 0, hkc = lane - 6 * hside;
  uint32_t hsrcA = hb + hside * HSIDE + (1 + w) * 96 + hkc * 16;
  const uint32_t hoffB = ((w < 2 ? 2 : 1) - w) * 96;
  const uint32_t hsgn = (w == 1) ? 0x3f803f80u : 0xbf80bf80u;
  const int hslot = (w == 1 || w == 2) ? w : ((w == 0) != (rank != 0) ? 0 : 3);
  const uint32_t hdst = tb + hslot * TPOS + hkc * PLANE + (hside ? 65 * 16 : 0);

  unsigned char* optr = (unsigned char*)out + (((size_t)(y0 + rank) * IMG) + x0 + 16 * w + g) * 192 + 16 * q;
  const bool last_block = (y0 + 32 == IMG);

#pragma unroll 1
  for (int s = 0; s < NSTEP; s++) {
    make_frags(fa, ca, zero);
    make_frags(fb, cb, zero);
    {
      const bool lastb = last_block && s == NSTEP - 2;
      if (s + 1 < NSTEP) cptr += 2 * 98304;
      const unsigned char* cptr2 = cptr + ((lastb || (last_block && s == NSTEP - 1)) ? 0 : 98304);
#pragma unroll
      for (int h = 0; h < 2; h++)
#pragma unroll
        for (int i = 0; i < 3; i++) {
          ca.v[h][i] = ldg128(cptr + h * 192 + 64 * i);
          cb.v[h][i] = ldg128(cptr2 + h * 192 + 64 * i);
        }
      if (s + 1 < NSTEP) pptr += 49152;
    }
    wg_fence();
    lateral_issue<0>(ax, fa, dwl);
    lateral_issue<24>(ax, fb, dwl);
    wg_commit();
    wg_wait<0>();
    fence_regs(ax);
    if (t128 == 0) mbar_expect_tx(bar_full, X_BYTES);
    lateral_finish<0>(ax, pa, d2);
    lateral_finish<24>(ax, pb, d3);
    if (last_block && s == NSTEP - 1) {
#pragma unroll
      for (int i = 0; i < 12; i++) d3[i] = 0;
    }
    {
      const unsigned char* pptr2 = pptr + ((last_block && s >= NSTEP - 2) ? 0 : 49152);
#pragma unroll
      for (int jj = 0; jj < 3; jj++) {
        pa[jj] = ldg64(pptr + 32 * jj);
        pb[jj] = ldg64(pptr2 + 32 * jj);
      }
    }
    mbar_wait_cluster(bar_empty, (s & 1) ^ 1);
    bar_wg(1 + wg);
#pragma unroll
    for (int h = 0; h < 2; h++)
#pragma unroll
      for (int jj = 0; jj < 3; jj++) {
        const int i0 = h * 6 + jj * 2;
        const uint32_t o = 2 * jj * PLANE + h * 16;
        sts64(ts + TPOS + o, hadd2(d1[i0], d2[i0]), hadd2(d1[i0 + 1], d2[i0 + 1]));
        sts64(ts + 2 * TPOS + o, hsub2(d2[i0], d1[i0]), hsub2(d2[i0 + 1], d1[i0 + 1]));
        sts64(ts0 + o, hsub2(d0[i0], d2[i0]), hsub2(d0[i0 + 1], d2[i0 + 1]));
        sts64(ts3 + o, hsub2(d3[i0], d1[i0]), hsub2(d3[i0 + 1], d1[i0 + 1]));
      }
    if (lane < 12) {
      const uint4 a = lds128(hsrcA), b = lds128(hsrcA + hoffB);
      sts128(hdst, hfma2(b.x, hsgn, a.x), hfma2(b.y, hsgn, a.y), hfma2(b.z, hsgn, a.z), hfma2(b.w, hsgn, a.w));
    }
    hsrcA += 192;
#pragma unroll
    for (int i = 0; i < 12; i++) {
      d0[i] = d2[i];
      d1[i] = d3[i];
    }
    fence_async_smem();
    bar_wg(1 + wg);

    wg_fence();
#pragma unroll
    for (int dj = 0; dj < 3; dj++)
#pragma unroll
      for (int ks = 0; ks < 3; ks++) {
        const uint64_t a1 = dA + (uint64_t)((1 * TPOS + 2 * ks * PLANE + dj * 16) >> 4);
        const uint64_t b1 = dB + (uint64_t)(((3 + dj) * UT + 2 * ks * 1536) >> 4);
        const uint64_t a2 = dA + (uint64_t)((2 * TPOS + 2 * ks * PLANE + dj * 16) >> 4);
        const uint64_t b2 = dB + (uint64_t)(((6 + dj) * UT + 2 * ks * 1536) >> 4);
        if (dj == 0 && ks == 0) {
          wgmma_ss_n96<true>(ax, a1, b1);
          wgmma_ss_n96<true>(ay, a2, b2);
        } else {
          wgmma_ss_n96<false>(ax, a1, b1);
          wgmma_ss_n96<false>(ay, a2, b2);
        }
      }
    wg_commit();
    wg_wait<0>();
    fence_regs(ax);
    fence_regs(ay);
#pragma unroll
    for (int i = 0; i < 48; i++) {
      const float a = ax[i], b = ay[i];
      ax[i] = a + b;
      ay[i] = a - b;
    }
    fence_regs(ax);
    fence_regs(ay);
    bar_wg(1 + wg);
    wg_fence();
#pragma unroll
    for (int dj = 0; dj < 3; dj++)
#pragma unroll
      for (int ks = 0; ks < 3; ks++)
        wgmma_ss_n96<false>(ay, dA + (uint64_t)((3 * TPOS + 2 * ks * PLANE + dj * 16) >> 4),
                            dB + (uint64_t)(((9 + dj) * UT + 2 * ks * 1536) >> 4));
    wg_commit();
#pragma unroll
    for (int dj = 0; dj < 3; dj++)
#pragma unroll
      for (int ks = 0; ks < 3; ks++)
        wgmma_ss_n96<false>(ax, dA + (uint64_t)((0 * TPOS + 2 * ks * PLANE + dj * 16) >> 4),
                            dB + (uint64_t)(((0 + dj) * UT + 2 * ks * 1536) >> 4));
    wg_commit();
    wg_wait<1>();
    fence_regs(ay);
#pragma unroll
    for (int h = 0; h < 2; h++)
#pragma unroll
      for (int J = 0; J < 3; J++) {
        const int b = 16 * J + 2 * h;
        sts128(sw + lane * 16 + (h * 3 + J) * 512, pack_bf16(ay[b], ay[b + 1]), pack_bf16(ay[b + 4], ay[b + 5]),
               pack_bf16(ay[b + 8], ay[b + 9]), pack_bf16(ay[b + 12], ay[b + 13]));
      }
    fence_async_smem();
    __syncwarp();
    bulk_copy_cluster_pred(r_xw, sw, 3072, r_full, lane == 0);
    wg_wait<0>();
    fence_regs(ax);
    mbar_wait_cluster(bar_full, s & 1);
#pragma unroll
    for (int h = 0; h < 2; h++)
#pragma unroll
      for (int J = 0; J < 3; J++) {
        const int b = 16 * J + 2 * h;
        const uint4 r = lds128(xb + (h * 3 + J) * 512);
        uint4 o;
        o.x = pack_bf16(ax[b] + bf_lo(r.x), ax[b + 1] + bf_hi(r.x));
        o.y = pack_bf16(ax[b + 4] + bf_lo(r.y), ax[b + 5] + bf_hi(r.y));
        o.z = pack_bf16(ax[b + 8] + bf_lo(r.z), ax[b + 9] + bf_hi(r.z));
        o.w = pack_bf16(ax[b + 12] + bf_lo(r.w), ax[b + 13] + bf_hi(r.w));
        *(uint4*)(optr + h * 8 * 192 + 64 * J) = o;
      }
    optr += 2 * 98304;
    __syncwarp();
    if (lane == 0) mbar_arrive_remote(r_empty);
  }
  cluster_arrive();
  cluster_wait();
}

}

extern "C" void kernel_launch(void* const* d_in, const int* in_sizes, int n_in, void* d_out, int out_size) {
  (void)in_sizes;
  (void)n_in;
  (void)out_size;
  static bool attr_done = false;
  if (!attr_done) {
    cudaFuncSetAttribute(fpn_kernel, cudaFuncAttributeMaxDynamicSharedMemorySize, SMEM_BYTES);
    attr_done = true;
  }
  fpn_kernel<<<128, 256, SMEM_BYTES, cudaStreamPerThread>>>(
      (const __nv_bfloat16*)d_in[0], (const __nv_bfloat16*)d_in[1], (const __nv_bfloat16*)d_in[2],
      (const __nv_bfloat16*)d_in[3], (__nv_bfloat16*)d_out, 0u);
}
```

```cpp
#include <cuda_runtime.h>
#include <cuda.h>
#include <cuda_bf16.h>
#include <stdint.h>

namespace {

constexpr int IMG = 512;
constexpr int CSLOT = 12288;
constexpr int UT = 9216;
constexpr int OFF_C = 0;
constexpr int OFF_U = 4 * CSLOT;
constexpr int OFF_WL = OFF_U + 12 * UT;
constexpr int OFF_X = OFF_WL + 9216;
constexpr int XROW = 6144;
constexpr int HTILE = 7680;
constexpr int X_BYTES = 2 * HTILE;
constexpr int OFF_H = OFF_X + 2 * X_BYTES;
constexpr int HSIDE = 35 * 128;
constexpr int H_BYTES = 2 * HSIDE;
constexpr int OFF_E = OFF_H + 2 * H_BYTES;
constexpr int EPAR = 1024;
constexpr int E_BYTES = 2 * EPAR;
constexpr int OFF_BAR = OFF_E + 2 * E_BYTES;
constexpr int SMEM_BYTES = OFF_BAR + 128;
constexpr int NSTEP = 16;

#define R4(c, a, o) c(a[o]), c(a[o + 1]), c(a[o + 2]), c(a[o + 3])
#define R8(c, a, o) R4(c, a, o), R4(c, a, o + 4)
#define R24(c, a, o) R8(c, a, o), R8(c, a, o + 8), R8(c, a, o + 16)
#define RL24 \
  "%0, %1, %2, %3, %4, %5, %6, %7, %8, %9, %10, %11, %12, %13, %14, %15, %16, %17, %18, %19, %20, %21, %22, %23"
#define RL48                                                                                                       \
  RL24 ", %24, %25, %26, %27, %28, %29, %30, %31, %32, %33, %34, %35, %36, %37, %38, %39, %40, %41, %42, %43, %44, " \
       "%45, %46, %47"

template <bool INIT>
__device__ __forceinline__ void wgmma_rs_n96(float (&d)[48], uint32_t a0, uint32_t a1, uint32_t a2, uint32_t a3,
                                             uint64_t db) {
  if constexpr (INIT) {
    asm volatile(
        "{\n.reg .pred p;\nsetp.ne.b32 p, 0, 0;\n"
        "wgmma.mma_async.sync.aligned.m64n96k16.f32.bf16.bf16 {" RL48 "}, {%48, %49, %50, %51}, %52, p, 1, 1, 0;\n}\n"
        : R24("=f", d, 0), R24("=f", d, 24)
        : "r"(a0), "r"(a1), "r"(a2), "r"(a3), "l"(db));
  } else {
    asm volatile(
        "{\n.reg .pred p;\nsetp.eq.b32 p, 0, 0;\n"
        "wgmma.mma_async.sync.aligned.m64n96k16.f32.bf16.bf16 {" RL48 "}, {%48, %49, %50, %51}, %52, p, 1, 1, 0;\n}\n"
        : R24("+f", d, 0), R24("+f", d, 24)
        : "r"(a0), "r"(a1), "r"(a2), "r"(a3), "l"(db));
  }
}
template <bool INIT>
__device__ __forceinline__ void wgmma_ss_n48(float (&d)[24], uint64_t da, uint64_t db) {
  if constexpr (INIT) {
    asm volatile(
        "{\n.reg .pred p;\nsetp.ne.b32 p, 0, 0;\n"
        "wgmma.mma_async.sync.aligned.m64n48k16.f32.bf16.bf16 {" RL24 "}, %24, %25, p, 1, 1, 0, 0;\n}\n"
        : R24("=f", d, 0)
        : "l"(da), "l"(db));
  } else {
    asm volatile(
        "{\n.reg .pred p;\nsetp.eq.b32 p, 0, 0;\n"
        "wgmma.mma_async.sync.aligned.m64n48k16.f32.bf16.bf16 {" RL24 "}, %24, %25, p, 1, 1, 0, 0;\n}\n"
        : R24("+f", d, 0)
        : "l"(da), "l"(db));
  }
}
__device__ __forceinline__ void wg_fence() { asm volatile("wgmma.fence.sync.aligned;" ::: "memory"); }
__device__ __forceinline__ void wg_commit() { asm volatile("wgmma.commit_group.sync.aligned;" ::: "memory"); }
template <int N>
__device__ __forceinline__ void wg_wait() {
  asm volatile("wgmma.wait_group.sync.aligned %0;" ::"n"(N) : "memory");
}
template <int N>
__device__ __forceinline__ void fence_regs(float (&a)[N]) {
#pragma unroll
  for (int i = 0; i < N; i++) asm volatile("" : "+f"(a[i])::"memory");
}
__device__ __forceinline__ uint64_t make_desc(uint32_t saddr, uint32_t lbo, uint32_t sbo) {
  return (uint64_t)((saddr & 0x3FFFF) >> 4) | ((uint64_t)(lbo >> 4) << 16) | ((uint64_t)(sbo >> 4) << 32);
}
__device__ __forceinline__ void fence_async_smem() { asm volatile("fence.proxy.async.shared::cta;" ::: "memory"); }
__device__ __forceinline__ void bar_wg(int id) { asm volatile("bar.sync %0, 128;" ::"r"(id) : "memory"); }

__device__ __forceinline__ uint32_t pack_bf16(float lo, float hi) {
  uint32_t r;
  asm("cvt.rn.bf16x2.f32 %0, %1, %2;" : "=r"(r) : "f"(hi), "f"(lo));
  return r;
}
__device__ __forceinline__ uint32_t hadd2(uint32_t a, uint32_t b) {
  uint32_t r;
  asm("add.rn.bf16x2 %0, %1, %2;" : "=r"(r) : "r"(a), "r"(b));
  return r;
}
__device__ __forceinline__ uint32_t hsub2(uint32_t a, uint32_t b) {
  uint32_t r;
  asm("sub.rn.bf16x2 %0, %1, %2;" : "=r"(r) : "r"(a), "r"(b));
  return r;
}
__device__ __forceinline__ float bf_lo(uint32_t a) { return __uint_as_float(a << 16); }
__device__ __forceinline__ float bf_hi(uint32_t a) { return __uint_as_float(a & 0xffff0000u); }

__device__ __forceinline__ uint4 ldg128(const void* p) {
  uint4 v;
  asm volatile("ld.global.nc.L1::no_allocate.v4.u32 {%0,%1,%2,%3}, [%4];"
               : "=r"(v.x), "=r"(v.y), "=r"(v.z), "=r"(v.w)
               : "l"(p));
  return v;
}
__device__ __forceinline__ uint2 ldg64(const void* p) {
  uint2 v;
  asm volatile("ld.global.nc.L1::no_allocate.v2.u32 {%0,%1}, [%2];" : "=r"(v.x), "=r"(v.y) : "l"(p));
  return v;
}
__device__ __forceinline__ void sts128(uint32_t a, uint32_t x, uint32_t y, uint32_t z, uint32_t w) {
  asm volatile("st.shared.v4.u32 [%0], {%1,%2,%3,%4};" ::"r"(a), "r"(x), "r"(y), "r"(z), "r"(w) : "memory");
}
__device__ __forceinline__ void sts24_pred(uint32_t a, const uint32_t (&v)[6], uint32_t pred) {
  asm volatile(
      "{\n.reg .pred p;\nsetp.ne.b32 p, %7, 0;\n"
      "@p st.shared.v4.u32 [%0], {%1,%2,%3,%4};\n"
      "@p st.shared.v2.u32 [%0+16], {%5,%6};\n}\n" ::"r"(a),
      "r"(v[0]), "r"(v[1]), "r"(v[2]), "r"(v[3]), "r"(v[4]), "r"(v[5]), "r"(pred)
      : "memory");
}
__device__ __forceinline__ void lds24_pred(uint32_t a, uint32_t (&v)[6], uint32_t pred) {
  asm volatile(
      "{\n.reg .pred p;\nsetp.ne.b32 p, %7, 0;\n"
      "@p ld.shared.v4.u32 {%0,%1,%2,%3}, [%6];\n"
      "@p ld.shared.v2.u32 {%4,%5}, [%6+16];\n}\n"
      : "+r"(v[0]), "+r"(v[1]), "+r"(v[2]), "+r"(v[3]), "+r"(v[4]), "+r"(v[5])
      : "r"(a), "r"(pred)
      : "memory");
}
__device__ __forceinline__ uint4 lds128(uint32_t a) {
  uint4 v;
  asm volatile("ld.shared.v4.u32 {%0,%1,%2,%3}, [%4];" : "=r"(v.x), "=r"(v.y), "=r"(v.z), "=r"(v.w) : "r"(a) : "memory");
  return v;
}
__device__ __forceinline__ void mbar_init(uint32_t bar, uint32_t cnt) {
  asm volatile("mbarrier.init.shared::cta.b64 [%0], %1;" ::"r"(bar), "r"(cnt) : "memory");
}
__device__ __forceinline__ void mbar_expect_tx(uint32_t bar, uint32_t bytes) {
  asm volatile("mbarrier.arrive.expect_tx.shared::cta.b64 _, [%0], %1;" ::"r"(bar), "r"(bytes) : "memory");
}
__device__ __forceinline__ void mbar_wait(uint32_t bar, uint32_t parity) {
  uint32_t ok;
  int it = 0;
  do {
    asm volatile(
        "{\n.reg .pred p;\n"
        "mbarrier.try_wait.parity.shared::cta.b64 p, [%1], %2;\n"
        "selp.u32 %0, 1, 0, p;\n}\n"
        : "=r"(ok)
        : "r"(bar), "r"(parity)
        : "memory");
    if (++it > (1 << 22)) __trap();
  } while (!ok);
}
__device__ __forceinline__ void mbar_arrive_remote(uint32_t rbar) {
  asm volatile("mbarrier.arrive.shared::cluster.b64 _, [%0];" ::"r"(rbar) : "memory");
}
__device__ __forceinline__ uint32_t mapa(uint32_t a, uint32_t rank) {
  uint32_t r;
  asm("mapa.shared::cluster.u32 %0, %1, %2;" : "=r"(r) : "r"(a), "r"(rank));
  return r;
}
__device__ __forceinline__ void st_async128(uint32_t ra, uint32_t x, uint32_t y, uint32_t z, uint32_t w, uint32_t rbar) {
  asm volatile("st.async.weak.shared::cluster.mbarrier::complete_tx::bytes.v4.b32 [%0], {%1,%2,%3,%4}, [%5];" ::"r"(ra),
               "r"(x), "r"(y), "r"(z), "r"(w), "r"(rbar)
               : "memory");
}
__device__ __forceinline__ void tma_row(uint32_t dst, const CUtensorMap* map, int grp, uint32_t bar) {
  asm volatile(
      "cp.async.bulk.tensor.5d.shared::cluster.global.mbarrier::complete_tx::bytes [%0], [%1, {%3, %3, %3, %4, %3}], "
      "[%2];" ::"r"(dst),
      "l"(map), "r"(bar), "r"(0), "r"(grp)
      : "memory");
}
__device__ __forceinline__ void tma_col(uint32_t dst, const CUtensorMap* map, int y, int x, uint32_t bar) {
  asm volatile(
      "cp.async.bulk.tensor.4d.shared::cluster.global.mbarrier::complete_tx::bytes [%0], [%1, {%3, %4, %3, %5}], "
      "[%2];" ::"r"(dst),
      "l"(map), "r"(bar), "r"(0), "r"(y), "r"(x)
      : "memory");
}
__device__ __forceinline__ void cluster_arrive() { asm volatile("barrier.cluster.arrive.release.aligned;" ::: "memory"); }
__device__ __forceinline__ void cluster_wait() { asm volatile("barrier.cluster.wait.acquire.aligned;" ::: "memory"); }

__device__ __forceinline__ uint32_t wsel(const uint4& v, int i) { return i == 0 ? v.x : i == 1 ? v.y : i == 2 ? v.z : v.w; }
__device__ __forceinline__ int cmap(int j, int q, int e) { return j < 4 ? 8 * q + 2 * j + e : 32 + 4 * q + 2 * (j - 4) + e; }

struct DRow {
  uint32_t o0[6], o1[6], nA[6], nB[6];
};
struct PRow {
  uint4 a;
  uint2 b;
};
__device__ __forceinline__ uint32_t pw(const PRow& p, int j) {
  return j == 0 ? p.a.x : j == 1 ? p.a.y : j == 2 ? p.a.z : j == 3 ? p.a.w : j == 4 ? p.b.x : p.b.y;
}
template <bool ADD>
__device__ __forceinline__ uint32_t top(uint32_t a, uint32_t b) {
  return ADD ? hadd2(a, b) : hsub2(a, b);
}
template <bool ADD>
__device__ __forceinline__ void frags(uint32_t (&f)[12], const DRow& a, const DRow& b, int ks) {
#pragma unroll
  for (int i = 0; i < 2; i++) {
    const int j = 2 * ks + i;
    const uint32_t t0 = top<ADD>(a.o0[j], b.o0[j]), t1 = top<ADD>(a.o1[j], b.o1[j]);
    f[0 + 2 * i] = top<ADD>(a.nA[j], b.nA[j]);
    f[1 + 2 * i] = t0;
    f[4 + 2 * i] = t0;
    f[5 + 2 * i] = t1;
    f[8 + 2 * i] = t1;
    f[9 + 2 * i] = top<ADD>(a.nB[j], b.nB[j]);
  }
}
template <bool INIT>
__device__ __forceinline__ void conv_group(float (&acc)[48], const uint32_t (&f)[12], uint64_t dB, int pos, int ks) {
  wg_fence();
  wgmma_rs_n96<INIT>(acc, f[0], f[1], f[2], f[3], dB + (uint64_t)(((3 * pos + 0) * UT + 2 * ks * 1536) >> 4));
  wgmma_rs_n96<false>(acc, f[4], f[5], f[6], f[7], dB + (uint64_t)(((3 * pos + 1) * UT + 2 * ks * 1536) >> 4));
  wgmma_rs_n96<false>(acc, f[8], f[9], f[10], f[11], dB + (uint64_t)(((3 * pos + 2) * UT + 2 * ks * 1536) >> 4));
  wg_commit();
}
template <int CH>
__device__ __forceinline__ void lateral(float (&acc)[24], uint64_t dA, uint64_t dwl) {
  wg_fence();
#pragma unroll
  for (int k = 0; k < 6; k++) {
    const uint64_t a = dA + (uint64_t)(((k >> 1) * CH + (k & 1) * 32) >> 4);
    const uint64_t b = dwl + (uint64_t)(k * 1536 >> 4);
    if (k == 0)
      wgmma_ss_n48<true>(acc, a, b);
    else
      wgmma_ss_n48<false>(acc, a, b);
  }
  wg_commit();
}

template <int V>
struct IC {
  static constexpr int value = V;
};

__global__ void __cluster_dims__(2, 1, 1) __launch_bounds__(256, 1)
    fpn_kernel(const __grid_constant__ CUtensorMap map_row, const __grid_constant__ CUtensorMap map_col,
               const __nv_bfloat16* __restrict__ p_coarse, const __nv_bfloat16* __restrict__ w_lat,
               const __nv_bfloat16* __restrict__ w_out, __nv_bfloat16* __restrict__ out) {
  extern __shared__ __align__(1024) unsigned char smem[];
  const uint32_t sb = (uint32_t)__cvta_generic_to_shared(smem);
  const int tid = threadIdx.x;
  const int wg = __shfl_sync(0xffffffffu, tid >> 7, 0);
  const int t128 = tid & 127;
  const int w = __shfl_sync(0xffffffffu, (tid >> 5) & 3, 0);
  const int lane = tid & 31;
  const int g = lane >> 2, q = lane & 3;
  uint32_t rank;
  asm("mov.u32 %0, %%cluster_ctarank;" : "=r"(rank));
  const int cl = blockIdx.x >> 1;
  const int y0 = (cl >> 2) * 32;
  const int x0 = ((cl & 3) * 2 + wg) * 64;

  if (tid == 0) {
#pragma unroll
    for (int i = 0; i < 2; i++) {
      const uint32_t b = sb + OFF_BAR + i * 64;
      mbar_init(b + 0, 1);
      mbar_init(b + 8, 1);
      mbar_init(b + 16, 1);
      mbar_init(b + 24, 1);
      mbar_init(b + 32, 4);
      mbar_init(b + 40, 4);
      mbar_init(b + 48, 1);
    }
    asm volatile("fence.mbarrier_init.release.cluster;" ::: "memory");
    fence_async_smem();
#pragma unroll
    for (int i = 0; i < 2; i++) {
      const uint32_t b = sb + OFF_BAR + i * 64;
      const int xw = ((cl & 3) * 2 + i) * 64;
      mbar_expect_tx(b + 48, 2 * HTILE);
      tma_col(sb + OFF_X + i * X_BYTES, &map_col, y0 - 1, xw - 1, b + 48);
      tma_col(sb + OFF_X + i * X_BYTES + HTILE, &map_col, y0 - 1, xw + 64, b + 48);
      mbar_expect_tx(b + 0, CSLOT);
      tma_row(sb + OFF_C + i * 2 * CSLOT, &map_row, (y0 - 1) * 32 + (xw >> 4), b + 0);
      mbar_expect_tx(b + 8, CSLOT);
      tma_row(sb + OFF_C + i * 2 * CSLOT + CSLOT, &map_row, y0 * 32 + (xw >> 4), b + 8);
      mbar_expect_tx(b + 16, XROW);
      mbar_expect_tx(b + 24, XROW);
    }
  }
  cluster_arrive();

  const unsigned char* pc = (const unsigned char*)p_coarse + 96 * rank;

  PRow hp[2][2], pA, pp;
  bool hv[2][2];
#pragma unroll
  for (int sd = 0; sd < 2; sd++)
#pragma unroll
    for (int h = 0; h < 2; h++) {
      const int hr = 16 * w + 8 * h + g, yy = y0 - 1 + hr, xx = sd ? x0 + 64 : x0 - 1;
      hv[sd][h] = hr < 34 && yy >= 0 && yy < IMG && xx >= 0 && xx < IMG;
      const unsigned char* a = pc + (hv[sd][h] ? ((size_t)(yy >> 1) * 256 + (xx >> 1)) * 192 : 0);
      hp[sd][h].a = ldg128(a + 16 * q);
      hp[sd][h].b = ldg64(a + 64 + 8 * q);
    }
  const unsigned char* pptr = pc + ((size_t)(y0 >> 1) * 256 + (x0 >> 1) + 8 * w + g) * 192;
  {
    const unsigned char* a = pptr - (y0 > 0 ? 49152 : 0);
    pA.a = ldg128(a + 16 * q);
    pA.b = ldg64(a + 64 + 8 * q);
    pp.a = ldg128(pptr + 16 * q);
    pp.b = ldg64(pptr + 64 + 8 * q);
  }

  if (tid < 216) {
    const int dj = tid / 72, rem = tid % 72, kc = rem / 12, u = rem % 12;
    const unsigned char* src = (const unsigned char*)w_out + ((size_t)(dj * 96 + 48 * rank) * 96 + 8 * u) * 2;
    uint4 v[3][8];
#pragma unroll
    for (int kk = 0; kk < 8; kk++) {
      const int ci = cmap(kc, kk >> 1, kk & 1);
#pragma unroll
      for (int di = 0; di < 3; di++) v[di][kk] = ldg128(src + (size_t)di * 3 * 96 * 192 + ci * 192);
    }
    const uint32_t base = sb + OFF_U + dj * UT + kc * 1536 + (8 * (4 * (u >> 2)) + 2 * (u & 3)) * 16;
#pragma unroll
    for (int wd = 0; wd < 4; wd++) {
      uint32_t u0[2][4], u1[2][4], u2[2][4], u3[2][4];
#pragma unroll
      for (int kp = 0; kp < 4; kp++) {
        const uint32_t a0 = wsel(v[0][2 * kp], wd), a1 = wsel(v[0][2 * kp + 1], wd);
        const uint32_t b0 = wsel(v[1][2 * kp], wd), b1 = wsel(v[1][2 * kp + 1], wd);
        const uint32_t c0 = wsel(v[2][2 * kp], wd), c1 = wsel(v[2][2 * kp + 1], wd);
        u0[0][kp] = __byte_perm(a0, a1, 0x5410);
        u0[1][kp] = __byte_perm(a0, a1, 0x7632);
        u3[0][kp] = __byte_perm(c0, c1, 0x5410);
        u3[1][kp] = __byte_perm(c0, c1, 0x7632);
        const float s0l = bf_lo(a0) + bf_lo(c0), s1l = bf_lo(a1) + bf_lo(c1);
        const float s0h = bf_hi(a0) + bf_hi(c0), s1h = bf_hi(a1) + bf_hi(c1);
        u1[0][kp] = pack_bf16((s0l + bf_lo(b0)) * 0.5f, (s1l + bf_lo(b1)) * 0.5f);
        u1[1][kp] = pack_bf16((s0h + bf_hi(b0)) * 0.5f, (s1h + bf_hi(b1)) * 0.5f);
        u2[0][kp] = pack_bf16((s0l - bf_lo(b0)) * 0.5f, (s1l - bf_lo(b1)) * 0.5f);
        u2[1][kp] = pack_bf16((s0h - bf_hi(b0)) * 0.5f, (s1h - bf_hi(b1)) * 0.5f);
      }
#pragma unroll
      for (int e = 0; e < 2; e++) {
        const uint32_t a = base + (8 * wd + e) * 16;
        sts128(a, u0[e][0], u0[e][1], u0[e][2], u0[e][3]);
        sts128(a + 3 * UT, u1[e][0], u1[e][1], u1[e][2], u1[e][3]);
        sts128(a + 6 * UT, u2[e][0], u2[e][1], u2[e][2], u2[e][3]);
        sts128(a + 9 * UT, u3[e][0], u3[e][1], u3[e][2], u3[e][3]);
      }
    }
  } else {
    for (int blk = tid - 216; blk < 72; blk += 40) {
      const int kc = blk / 6, u = blk % 6;
      uint4 v[8];
#pragma unroll
      for (int kk = 0; kk < 8; kk++)
        v[kk] = ldg128((const unsigned char*)w_lat + ((size_t)(8 * kc + kk) * 96 + 48 * rank + 8 * u) * 2);
#pragma unroll
      for (int wd = 0; wd < 4; wd++) {
        const int n = u < 4 ? 8 * wd + 2 * u : 8 * (4 + (wd & 1)) + 2 * (2 * (u - 4) + (wd >> 1));
        const uint32_t a = sb + OFF_WL + kc * 768 + n * 16;
        uint32_t lo[4], hi[4];
#pragma unroll
        for (int kp = 0; kp < 4; kp++) {
          lo[kp] = __byte_perm(wsel(v[2 * kp], wd), wsel(v[2 * kp + 1], wd), 0x5410);
          hi[kp] = __byte_perm(wsel(v[2 * kp], wd), wsel(v[2 * kp + 1], wd), 0x7632);
        }
        sts128(a, lo[0], lo[1], lo[2], lo[3]);
        sts128(a + 16, hi[0], hi[1], hi[2], hi[3]);
      }
    }
  }
  fence_async_smem();
  __syncthreads();
  cluster_wait();

  const uint32_t bb = sb + OFF_BAR + wg * 64;
  const uint64_t SW64 = (uint64_t)2 << 62;
  const uint64_t dwl = make_desc(sb + OFF_WL, 768, 128);
  const uint64_t dB = make_desc(sb + OFF_U, 1536, 128);
  const uint32_t cs = sb + OFF_C + wg * 2 * CSLOT;
  const uint64_t dC = make_desc(cs, 16, 512) | SW64;
  const uint32_t xbase = sb + OFF_X + wg * X_BYTES;
  const uint64_t dH = make_desc(xbase, 16, 512) | SW64;
  const uint32_t hb = sb + OFF_H + wg * H_BYTES;
  const uint32_t eb = sb + OFF_E + wg * E_BYTES;
  const uint32_t xa = xbase + t128 * 16;
  const uint32_t peer = rank ^ 1;
  const uint32_t r_xa = mapa(xa, peer);
  const uint32_t r_bb = mapa(bb, peer);
  const int grp0 = (y0 - 1) * 32 + (x0 >> 4);
  const bool last_block = (y0 + 32 == IMG);

  const uint32_t e0 = g == 0, e7 = g == 7;
  const bool halo_lane = (w == 0 && g == 0) || (w == 3 && g == 7);
  const uint32_t ewr = eb + w * 256 + (e7 ? 128 : 0) + 32 * q;
  uint32_t erd = (halo_lane ? (e0 ? hb : hb + HSIDE) : (e0 ? eb + (w - 1) * 256 + 128 : eb + (w + 1) * 256)) + 32 * q;
  const uint32_t edelta = halo_lane ? 128 : EPAR;
  const uint32_t eadv = halo_lane ? 256 : 0;

  float ax[48], ay[48], lat[24];
  DRow D0, D1, D2, D3;
  uint32_t k0[12], k1[12];
  uint32_t fr0[12], fr1[12];

  auto d_finish = [&](auto ODD, DRow& d, const float(&acc)[24], const PRow& p, bool zero, int inext) {
    constexpr int odd = decltype(ODD)::value;
#pragma unroll
    for (int j = 0; j < 6; j++) {
      d.o0[j] = hadd2(pack_bf16(acc[4 * j], acc[4 * j + 1]), pw(p, j));
      d.o1[j] = hadd2(pack_bf16(acc[4 * j + 2], acc[4 * j + 3]), pw(p, j));
    }
    if (zero) {
#pragma unroll
      for (int j = 0; j < 6; j++) d.o0[j] = d.o1[j] = 0;
    }
    uint32_t ev[6];
#pragma unroll
    for (int j = 0; j < 6; j++) ev[j] = e0 ? d.o0[j] : d.o1[j];
    sts24_pred(ewr + odd * EPAR, ev, e0 | e7);
#pragma unroll
    for (int j = 0; j < 6; j++) {
      d.nA[j] = __shfl_up_sync(0xffffffffu, d.o1[j], 4);
      d.nB[j] = __shfl_down_sync(0xffffffffu, d.o0[j], 4);
    }
    bar_wg(1 + wg);
    if (t128 == 0 && inext <= 33) {
      mbar_expect_tx(bb + odd * 8, CSLOT);
      tma_row(cs + odd * CSLOT, &map_row, grp0 + inext * 32, bb + odd * 8);
    }
    const uint32_t ra = odd ? erd + edelta : erd;
    lds24_pred(ra, d.nA, e0);
    lds24_pred(ra, d.nB, e7);
    if (odd) erd += eadv;
  };
  auto send = [&](const float(&acc)[48], uint32_t(&k)[12], int b, uint32_t parity) {
    uint32_t sd[12];
#pragma unroll
    for (int j = 0; j < 12; j++) {
      const uint32_t lo = pack_bf16(acc[4 * j], acc[4 * j + 1]), hi = pack_bf16(acc[4 * j + 2], acc[4 * j + 3]);
      k[j] = rank ? hi : lo;
      sd[j] = rank ? lo : hi;
    }
    mbar_wait(bb + 32 + 8 * b, parity);
#pragma unroll
    for (int J = 0; J < 3; J++)
      st_async128(r_xa + b * XROW + J * 2048, sd[4 * J], sd[4 * J + 1], sd[4 * J + 2], sd[4 * J + 3], r_bb + 16 + 8 * b);
  };
  unsigned char* optr = (unsigned char*)out + (((size_t)y0 * IMG) + x0 + 16 * w + 2 * g + rank) * 192 + 16 * q;
  auto finalize = [&](const uint32_t(&k)[12], int b, uint32_t parity) {
    mbar_wait(bb + 16 + 8 * b, parity);
    if (t128 == 0) mbar_expect_tx(bb + 16 + 8 * b, XROW);
#pragma unroll
    for (int J = 0; J < 3; J++) {
      const uint4 r = lds128(xa + b * XROW + J * 2048);
      uint4 o;
      o.x = hadd2(k[4 * J], r.x);
      o.y = hadd2(k[4 * J + 1], r.y);
      o.z = hadd2(k[4 * J + 2], r.z);
      o.w = hadd2(k[4 * J + 3], r.w);
      *(uint4*)(optr + b * 98304 + 64 * J) = o;
    }
    __syncwarp();
    if (lane == 0) mbar_arrive_remote(r_bb + 32 + 8 * b);
  };

  {
    float lat2[24];
    mbar_wait(bb + 48, 0);
    lateral<2560>(lat, dH, dwl);
    lateral<2560>(lat2, dH + (uint64_t)(HTILE >> 4), dwl);
    wg_wait<0>();
    fence_regs(lat);
    fence_regs(lat2);
    __syncwarp();
    if (lane == 0) {
      mbar_arrive_remote(r_bb + 32);
      mbar_arrive_remote(r_bb + 40);
    }
#pragma unroll
    for (int h = 0; h < 2; h++) {
      const int hr = 16 * w + 8 * h + g;
      uint32_t v0[6], v1[6];
#pragma unroll
      for (int j = 0; j < 6; j++) {
        v0[j] = hv[0][h] ? hadd2(pack_bf16(lat[4 * j + 2 * h], lat[4 * j + 2 * h + 1]), pw(hp[0][h], j)) : 0u;
        v1[j] = hv[1][h] ? hadd2(pack_bf16(lat2[4 * j + 2 * h], lat2[4 * j + 2 * h + 1]), pw(hp[1][h], j)) : 0u;
      }
      sts24_pred(hb + hr * 128 + 32 * q, v0, hr < 34);
      sts24_pred(hb + HSIDE + hr * 128 + 32 * q, v1, hr < 34);
    }
    mbar_wait(bb + 0, 0);
    lateral<4096>(lat, dC, dwl);
    mbar_wait(bb + 8, 0);
    lateral<4096>(lat2, dC + (uint64_t)(CSLOT >> 4), dwl);
    wg_wait<0>();
    fence_regs(lat);
    fence_regs(lat2);
    d_finish(IC<0>{}, D0, lat, pA, y0 == 0, 2);
    d_finish(IC<1>{}, D1, lat2, pp, false, 3);
    mbar_wait(bb + 0, 1);
    lateral<4096>(lat, dC, dwl);
    wg_wait<0>();
    fence_regs(lat);
    d_finish(IC<0>{}, D2, lat, pp, false, 4);
    pptr += 49152;
    pp.a = ldg128(pptr + 16 * q);
    pp.b = ldg64(pptr + 64 + 8 * q);
    frags<true>(fr0, D1, D2, 0);
    conv_group<true>(ax, fr0, dB, 1, 0);
  }

  auto step = [&](auto PARC, DRow& d0, DRow& d1, DRow& d2, DRow& d3, int s) {
    constexpr uint32_t PAR = decltype(PARC)::value;
    const bool notfirst = PAR ? true : s > 0;
    const bool notlast = PAR ? s < NSTEP - 1 : true;
    wg_wait<1>();
    fence_regs(ay);
    if (notfirst) send(ay, k1, 1, PAR ^ 1);
    frags<false>(fr1, d2, d1, 0);
    conv_group<true>(ay, fr1, dB, 2, 0);
    wg_wait<1>();
    frags<true>(fr0, d1, d2, 1);
    conv_group<false>(ax, fr0, dB, 1, 1);
    if (notfirst) finalize(k0, 0, PAR ^ 1);
    wg_wait<1>();
    frags<false>(fr1, d2, d1, 1);
    conv_group<false>(ay, fr1, dB, 2, 1);
    wg_wait<1>();
    frags<true>(fr0, d1, d2, 2);
    conv_group<false>(ax, fr0, dB, 1, 2);
    if (notfirst) {
      finalize(k1, 1, PAR ^ 1);
      optr += 2 * 98304;
    }
    wg_wait<1>();
    frags<false>(fr1, d2, d1, 2);
    conv_group<false>(ay, fr1, dB, 2, 2);
    mbar_wait(bb + 8, PAR ^ 1);
    lateral<4096>(lat, dC + (uint64_t)(CSLOT >> 4), dwl);
    wg_wait<2>();
    frags<false>(fr0, d0, d2, 0);
    wg_wait<1>();
    fence_regs(ax);
    fence_regs(ay);
#pragma unroll
    for (int i = 0; i < 48; i++) {
      const float a = ax[i], b = ay[i];
      ax[i] = a + b;
      ay[i] = a - b;
    }
    fence_regs(ax);
    fence_regs(ay);
    conv_group<false>(ax, fr0, dB, 0, 0);
    frags<false>(fr1, d0, d2, 1);
    conv_group<false>(ax, fr1, dB, 0, 1);
    wg_wait<1>();
    fence_regs(lat);
    frags<false>(fr0, d0, d2, 2);
    conv_group<false>(ax, fr0, dB, 0, 2);
    d_finish(IC<1>{}, d3, lat, pp, last_block && !notlast, 2 * s + 5);
    if (notlast) mbar_wait(bb + 0, PAR);
    lateral<4096>(lat, dC, dwl);
    wg_wait<2>();
    frags<false>(fr1, d3, d1, 0);
    conv_group<false>(ay, fr1, dB, 3, 0);
    wg_wait<2>();
    fence_regs(ax);
    frags<false>(fr0, d3, d1, 1);
    conv_group<false>(ay, fr0, dB, 3, 1);
    send(ax, k0, 0, PAR);
    wg_wait<1>();
    fence_regs(lat);
    frags<false>(fr1, d3, d1, 2);
    conv_group<false>(ay, fr1, dB, 3, 2);
    d_finish(IC<0>{}, d0, lat, pp, false, 2 * s + 6);
    if ((y0 >> 1) + s + 2 < 256) pptr += 49152;
    pp.a = ldg128(pptr + 16 * q);
    pp.b = ldg64(pptr + 64 + 8 * q);
    wg_wait<1>();
    frags<true>(fr0, d3, d0, 0);
    conv_group<true>(ax, fr0, dB, 1, 0);
  };

#pragma unroll 1
  for (int s = 0; s < NSTEP; s += 2) {
    step(IC<0>{}, D0, D1, D2, D3, s);
    step(IC<1>{}, D2, D3, D0, D1, s + 1);
  }
  wg_wait<0>();
  fence_regs(ax);
  fence_regs(ay);
  send(ay, k1, 1, 1);
  finalize(k0, 0, 1);
  finalize(k1, 1, 1);
  cluster_arrive();
  cluster_wait();
}

typedef CUresult (*EncodeFn)(CUtensorMap*, CUtensorMapDataType, cuuint32_t, void*, const cuuint64_t*, const cuuint64_t*,
                             const cuuint32_t*, const cuuint32_t*, CUtensorMapInterleave, CUtensorMapSwizzle,
                             CUtensorMapL2promotion, CUtensorMapFloatOOBfill);

}

extern "C" void kernel_launch(void* const* d_in, const int* in_sizes, int n_in, void* d_out, int out_size) {
  (void)in_sizes;
  (void)n_in;
  (void)out_size;
  static EncodeFn encode = nullptr;
  if (!encode) {
    cudaFuncSetAttribute(fpn_kernel, cudaFuncAttributeMaxDynamicSharedMemorySize, SMEM_BYTES);
    void* fn = nullptr;
    cudaDriverEntryPointQueryResult st;
    cudaGetDriverEntryPoint("cuTensorMapEncodeTiled", &fn, cudaEnableDefault, &st);
    encode = (EncodeFn)fn;
  }
  CUtensorMap map_row, map_col;
  {
    const cuuint64_t dim[5] = {32, 8, 2, 16384, 3};
    const cuuint64_t str[4] = {384, 192, 3072, 64};
    const cuuint32_t box[5] = {32, 8, 2, 4, 3};
    const cuuint32_t es[5] = {1, 1, 1, 1, 1};
    encode(&map_row, CU_TENSOR_MAP_DATA_TYPE_BFLOAT16, 5, d_in[0], dim, str, box, es, CU_TENSOR_MAP_INTERLEAVE_NONE,
           CU_TENSOR_MAP_SWIZZLE_64B, CU_TENSOR_MAP_L2_PROMOTION_L2_256B, CU_TENSOR_MAP_FLOAT_OOB_FILL_NONE);
  }
  {
    const cuuint64_t dim[4] = {32, 512, 3, 512};
    const cuuint64_t str[3] = {98304, 64, 192};
    const cuuint32_t box[4] = {32, 40, 3, 1};
    const cuuint32_t es[4] = {1, 1, 1, 1};
    encode(&map_col, CU_TENSOR_MAP_DATA_TYPE_BFLOAT16, 4, d_in[0], dim, str, box, es, CU_TENSOR_MAP_INTERLEAVE_NONE,
           CU_TENSOR_MAP_SWIZZLE_64B, CU_TENSOR_MAP_L2_PROMOTION_L2_128B, CU_TENSOR_MAP_FLOAT_OOB_FILL_NONE);
  }
  fpn_kernel<<<128, 256, SMEM_BYTES, cudaStreamPerThread>>>(map_row, map_col, (const __nv_bfloat16*)d_in[1],
                                                            (const __nv_bfloat16*)d_in[2], (const __nv_bfloat16*)d_in[3],
                                                            (__nv_bfloat16*)d_out);
}
```

```cpp
#include <cuda_runtime.h>
#include <cuda.h>
#include <cuda_bf16.h>
#include <stdint.h>

namespace {

constexpr int IMG = 512;
constexpr int CSLOT = 12288;
constexpr int UT = 9216;
constexpr int OFF_C = 0;
constexpr int OFF_U = 4 * CSLOT;
constexpr int OFF_WL = OFF_U + 12 * UT;
constexpr int OFF_X = OFF_WL + 9216;
constexpr int XROW = 6144;
constexpr int HTILE = 7680;
constexpr int X_BYTES = 2 * HTILE;
constexpr int OFF_H = OFF_X + 2 * X_BYTES;
constexpr int HSIDE = 35 * 128;
constexpr int H_BYTES = 2 * HSIDE;
constexpr int OFF_E = OFF_H + 2 * H_BYTES;
constexpr int EPAR = 1024;
constexpr int E_BYTES = 2 * EPAR;
constexpr int OFF_BAR = OFF_E + 2 * E_BYTES;
constexpr int SMEM_BYTES = OFF_BAR + 128;
constexpr int NSTEP = 16;

#define R4(c, a, o) c(a[o]), c(a[o + 1]), c(a[o + 2]), c(a[o + 3])
#define R8(c, a, o) R4(c, a, o), R4(c, a, o + 4)
#define R24(c, a, o) R8(c, a, o), R8(c, a, o + 8), R8(c, a, o + 16)
#define RL24 \
  "%0, %1, %2, %3, %4, %5, %6, %7, %8, %9, %10, %11, %12, %13, %14, %15, %16, %17, %18, %19, %20, %21, %22, %23"
#define RL48                                                                                                       \
  RL24 ", %24, %25, %26, %27, %28, %29, %30, %31, %32, %33, %34, %35, %36, %37, %38, %39, %40, %41, %42, %43, %44, " \
       "%45, %46, %47"

constexpr uint32_t HI_W = 128 >> 4;
constexpr uint32_t HI_C = (512 >> 4) | (2u << 30);
template <bool INIT>
__device__ __forceinline__ void wgmma_rs_n96(float (&d)[48], uint32_t a0, uint32_t a1, uint32_t a2, uint32_t a3,
                                             uint32_t db) {
  if constexpr (INIT) {
    asm volatile(
        "{\n.reg .pred p;\n.reg .b64 db;\nsetp.ne.b32 p, 0, 0;\nmov.b64 db, {%52, %53};\n"
        "wgmma.mma_async.sync.aligned.m64n96k16.f32.bf16.bf16 {" RL48 "}, {%48, %49, %50, %51}, db, p, 1, 1, 0;\n}\n"
        : R24("=f", d, 0), R24("=f", d, 24)
        : "r"(a0), "r"(a1), "r"(a2), "r"(a3), "r"(db), "n"(HI_W));
  } else {
    asm volatile(
        "{\n.reg .pred p;\n.reg .b64 db;\nsetp.eq.b32 p, 0, 0;\nmov.b64 db, {%52, %53};\n"
        "wgmma.mma_async.sync.aligned.m64n96k16.f32.bf16.bf16 {" RL48 "}, {%48, %49, %50, %51}, db, p, 1, 1, 0;\n}\n"
        : R24("+f", d, 0), R24("+f", d, 24)
        : "r"(a0), "r"(a1), "r"(a2), "r"(a3), "r"(db), "n"(HI_W));
  }
}
template <bool INIT>
__device__ __forceinline__ void wgmma_ss_n48(float (&d)[24], uint32_t da, uint32_t db) {
  if constexpr (INIT) {
    asm volatile(
        "{\n.reg .pred p;\n.reg .b64 da, db;\nsetp.ne.b32 p, 0, 0;\nmov.b64 da, {%24, %26};\nmov.b64 db, {%25, %27};\n"
        "wgmma.mma_async.sync.aligned.m64n48k16.f32.bf16.bf16 {" RL24 "}, da, db, p, 1, 1, 0, 0;\n}\n"
        : R24("=f", d, 0)
        : "r"(da), "r"(db), "n"(HI_C), "n"(HI_W));
  } else {
    asm volatile(
        "{\n.reg .pred p;\n.reg .b64 da, db;\nsetp.eq.b32 p, 0, 0;\nmov.b64 da, {%24, %26};\nmov.b64 db, {%25, %27};\n"
        "wgmma.mma_async.sync.aligned.m64n48k16.f32.bf16.bf16 {" RL24 "}, da, db, p, 1, 1, 0, 0;\n}\n"
        : R24("+f", d, 0)
        : "r"(da), "r"(db), "n"(HI_C), "n"(HI_W));
  }
}
__device__ __forceinline__ void wg_fence() { asm volatile("wgmma.fence.sync.aligned;" ::: "memory"); }
__device__ __forceinline__ void wg_commit() { asm volatile("wgmma.commit_group.sync.aligned;" ::: "memory"); }
template <int N>
__device__ __forceinline__ void wg_wait() {
  asm volatile("wgmma.wait_group.sync.aligned %0;" ::"n"(N) : "memory");
}
template <int N>
__device__ __forceinline__ void fence_regs(float (&a)[N]) {
#pragma unroll
  for (int i = 0; i < N; i++) asm volatile("" : "+f"(a[i])::"memory");
}
__device__ __forceinline__ uint32_t make_desc(uint32_t saddr, uint32_t lbo) {
  return ((saddr & 0x3FFFF) >> 4) | ((lbo >> 4) << 16);
}
__device__ __forceinline__ void fence_async_smem() { asm volatile("fence.proxy.async.shared::cta;" ::: "memory"); }
__device__ __forceinline__ void bar_wg(int id) { asm volatile("bar.sync %0, 128;" ::"r"(id) : "memory"); }

__device__ __forceinline__ uint32_t pack_bf16(float lo, float hi) {
  uint32_t r;
  asm("cvt.rn.bf16x2.f32 %0, %1, %2;" : "=r"(r) : "f"(hi), "f"(lo));
  return r;
}
__device__ __forceinline__ uint32_t hadd2(uint32_t a, uint32_t b) {
  uint32_t r;
  asm("add.rn.bf16x2 %0, %1, %2;" : "=r"(r) : "r"(a), "r"(b));
  return r;
}
__device__ __forceinline__ uint32_t hsub2(uint32_t a, uint32_t b) {
  uint32_t r;
  asm("sub.rn.bf16x2 %0, %1, %2;" : "=r"(r) : "r"(a), "r"(b));
  return r;
}
__device__ __forceinline__ float bf_lo(uint32_t a) { return __uint_as_float(a << 16); }
__device__ __forceinline__ float bf_hi(uint32_t a) { return __uint_as_float(a & 0xffff0000u); }

__device__ __forceinline__ uint4 ldg128(const void* p) {
  uint4 v;
  asm volatile("ld.global.nc.L1::no_allocate.v4.u32 {%0,%1,%2,%3}, [%4];"
               : "=r"(v.x), "=r"(v.y), "=r"(v.z), "=r"(v.w)
               : "l"(p));
  return v;
}
__device__ __forceinline__ uint2 ldg64(const void* p) {
  uint2 v;
  asm volatile("ld.global.nc.L1::no_allocate.v2.u32 {%0,%1}, [%2];" : "=r"(v.x), "=r"(v.y) : "l"(p));
  return v;
}
__device__ __forceinline__ void sts128(uint32_t a, uint32_t x, uint32_t y, uint32_t z, uint32_t w) {
  asm volatile("st.shared.v4.u32 [%0], {%1,%2,%3,%4};" ::"r"(a), "r"(x), "r"(y), "r"(z), "r"(w) : "memory");
}
__device__ __forceinline__ void sts24_pred(uint32_t a, const uint32_t (&v)[6], uint32_t pred) {
  asm volatile(
      "{\n.reg .pred p;\nsetp.ne.b32 p, %7, 0;\n"
      "@p st.shared.v4.u32 [%0], {%1,%2,%3,%4};\n"
      "@p st.shared.v2.u32 [%0+16], {%5,%6};\n}\n" ::"r"(a),
      "r"(v[0]), "r"(v[1]), "r"(v[2]), "r"(v[3]), "r"(v[4]), "r"(v[5]), "r"(pred)
      : "memory");
}
__device__ __forceinline__ void lds24_pred(uint32_t a, uint32_t (&v)[6], uint32_t pred) {
  asm volatile(
      "{\n.reg .pred p;\nsetp.ne.b32 p, %7, 0;\n"
      "@p ld.shared.v4.u32 {%0,%1,%2,%3}, [%6];\n"
      "@p ld.shared.v2.u32 {%4,%5}, [%6+16];\n}\n"
      : "+r"(v[0]), "+r"(v[1]), "+r"(v[2]), "+r"(v[3]), "+r"(v[4]), "+r"(v[5])
      : "r"(a), "r"(pred)
      : "memory");
}
__device__ __forceinline__ uint4 lds128(uint32_t a) {
  uint4 v;
  asm volatile("ld.shared.v4.u32 {%0,%1,%2,%3}, [%4];" : "=r"(v.x), "=r"(v.y), "=r"(v.z), "=r"(v.w) : "r"(a) : "memory");
  return v;
}
__device__ __forceinline__ void mbar_init(uint32_t bar, uint32_t cnt) {
  asm volatile("mbarrier.init.shared::cta.b64 [%0], %1;" ::"r"(bar), "r"(cnt) : "memory");
}
__device__ __forceinline__ void mbar_expect_tx(uint32_t bar, uint32_t bytes) {
  asm volatile("mbarrier.arrive.expect_tx.shared::cta.b64 _, [%0], %1;" ::"r"(bar), "r"(bytes) : "memory");
}
__device__ __forceinline__ void mbar_wait(uint32_t bar, uint32_t parity) {
  uint32_t ok;
  int it = 0;
  do {
    asm volatile(
        "{\n.reg .pred p;\n"
        "mbarrier.try_wait.parity.shared::cta.b64 p, [%1], %2;\n"
        "selp.u32 %0, 1, 0, p;\n}\n"
        : "=r"(ok)
        : "r"(bar), "r"(parity)
        : "memory");
    if (++it > (1 << 22)) __trap();
  } while (!ok);
}
__device__ __forceinline__ void mbar_arrive_remote(uint32_t rbar) {
  asm volatile("mbarrier.arrive.shared::cluster.b64 _, [%0];" ::"r"(rbar) : "memory");
}
__device__ __forceinline__ uint32_t mapa(uint32_t a, uint32_t rank) {
  uint32_t r;
  asm("mapa.shared::cluster.u32 %0, %1, %2;" : "=r"(r) : "r"(a), "r"(rank));
  return r;
}
__device__ __forceinline__ void st_async128(uint32_t ra, uint32_t x, uint32_t y, uint32_t z, uint32_t w, uint32_t rbar) {
  asm volatile("st.async.weak.shared::cluster.mbarrier::complete_tx::bytes.v4.b32 [%0], {%1,%2,%3,%4}, [%5];" ::"r"(ra),
               "r"(x), "r"(y), "r"(z), "r"(w), "r"(rbar)
               : "memory");
}
__device__ __forceinline__ void tma_row(uint32_t dst, const CUtensorMap* map, int grp, uint32_t bar) {
  asm volatile(
      "cp.async.bulk.tensor.5d.shared::cluster.global.mbarrier::complete_tx::bytes [%0], [%1, {%3, %3, %3, %4, %3}], "
      "[%2];" ::"r"(dst),
      "l"(map), "r"(bar), "r"(0), "r"(grp)
      : "memory");
}
__device__ __forceinline__ void tma_col(uint32_t dst, const CUtensorMap* map, int y, int x, uint32_t bar) {
  asm volatile(
      "cp.async.bulk.tensor.4d.shared::cluster.global.mbarrier::complete_tx::bytes [%0], [%1, {%3, %4, %3, %5}], "
      "[%2];" ::"r"(dst),
      "l"(map), "r"(bar), "r"(0), "r"(y), "r"(x)
      : "memory");
}
__device__ __forceinline__ void cluster_arrive() { asm volatile("barrier.cluster.arrive.release.aligned;" ::: "memory"); }
__device__ __forceinline__ void cluster_wait() { asm volatile("barrier.cluster.wait.acquire.aligned;" ::: "memory"); }

__device__ __forceinline__ uint32_t wsel(const uint4& v, int i) { return i == 0 ? v.x : i == 1 ? v.y : i == 2 ? v.z : v.w; }
__device__ __forceinline__ int cmap(int j, int q, int e) { return j < 4 ? 8 * q + 2 * j + e : 32 + 4 * q + 2 * (j - 4) + e; }

struct DRow {
  uint32_t o0[6], o1[6], nA[6], nB[6];
};
struct PRow {
  uint4 a;
  uint2 b;
};
__device__ __forceinline__ uint32_t pw(const PRow& p, int j) {
  return j == 0 ? p.a.x : j == 1 ? p.a.y : j == 2 ? p.a.z : j == 3 ? p.a.w : j == 4 ? p.b.x : p.b.y;
}
template <bool ADD>
__device__ __forceinline__ uint32_t top(uint32_t a, uint32_t b) {
  return ADD ? hadd2(a, b) : hsub2(a, b);
}
template <bool ADD>
__device__ __forceinline__ void frags(uint32_t (&f)[12], const DRow& a, const DRow& b, int ks) {
#pragma unroll
  for (int i = 0; i < 2; i++) {
    const int j = 2 * ks + i;
    const uint32_t t0 = top<ADD>(a.o0[j], b.o0[j]), t1 = top<ADD>(a.o1[j], b.o1[j]);
    f[0 + 2 * i] = top<ADD>(a.nA[j], b.nA[j]);
    f[1 + 2 * i] = t0;
    f[4 + 2 * i] = t0;
    f[5 + 2 * i] = t1;
    f[8 + 2 * i] = t1;
    f[9 + 2 * i] = top<ADD>(a.nB[j], b.nB[j]);
  }
}
template <bool INIT>
__device__ __forceinline__ void conv_group(float (&acc)[48], const uint32_t (&f)[12], uint32_t dB, int pos, int ks) {
  wg_fence();
  wgmma_rs_n96<INIT>(acc, f[0], f[1], f[2], f[3], dB + (uint32_t)(((3 * pos + 0) * UT + 2 * ks * 1536) >> 4));
  wgmma_rs_n96<false>(acc, f[4], f[5], f[6], f[7], dB + (uint32_t)(((3 * pos + 1) * UT + 2 * ks * 1536) >> 4));
  wgmma_rs_n96<false>(acc, f[8], f[9], f[10], f[11], dB + (uint32_t)(((3 * pos + 2) * UT + 2 * ks * 1536) >> 4));
  wg_commit();
}
template <int CH>
__device__ __forceinline__ void lateral(float (&acc)[24], uint32_t dA, uint32_t dwl) {
  wg_fence();
#pragma unroll
  for (int k = 0; k < 6; k++) {
    const uint32_t a = dA + (uint32_t)(((k >> 1) * CH + (k & 1) * 32) >> 4);
    const uint32_t b = dwl + (uint32_t)(k * 1536 >> 4);
    if (k == 0)
      wgmma_ss_n48<true>(acc, a, b);
    else
      wgmma_ss_n48<false>(acc, a, b);
  }
  wg_commit();
}

template <int V>
struct IC {
  static constexpr int value = V;
};

__global__ void __cluster_dims__(2, 1, 1) __launch_bounds__(256, 1)
    fpn_kernel(const __grid_constant__ CUtensorMap map_row, const __grid_constant__ CUtensorMap map_col,
               const __nv_bfloat16* __restrict__ p_coarse, const __nv_bfloat16* __restrict__ w_lat,
               const __nv_bfloat16* __restrict__ w_out, __nv_bfloat16* __restrict__ out) {
  extern __shared__ __align__(1024) unsigned char smem[];
  const uint32_t sb = (uint32_t)__cvta_generic_to_shared(smem);
  const int tid = threadIdx.x;
  const int wg = __shfl_sync(0xffffffffu, tid >> 7, 0);
  const int t128 = tid & 127;
  const int w = __shfl_sync(0xffffffffu, (tid >> 5) & 3, 0);
  const int lane = tid & 31;
  const int g = lane >> 2, q = lane & 3;
  uint32_t rank;
  asm("mov.u32 %0, %%cluster_ctarank;" : "=r"(rank));
  const int cl = blockIdx.x >> 1;
  const int y0 = (cl >> 2) * 32;
  const int x0 = ((cl & 3) * 2 + wg) * 64;

  if (tid == 0) {
#pragma unroll
    for (int i = 0; i < 2; i++) {
      const uint32_t b = sb + OFF_BAR + i * 64;
      mbar_init(b + 0, 1);
      mbar_init(b + 8, 1);
      mbar_init(b + 16, 1);
      mbar_init(b + 24, 1);
      mbar_init(b + 32, 4);
      mbar_init(b + 40, 4);
      mbar_init(b + 48, 1);
    }
    asm volatile("fence.mbarrier_init.release.cluster;" ::: "memory");
    fence_async_smem();
#pragma unroll
    for (int i = 0; i < 2; i++) {
      const uint32_t b = sb + OFF_BAR + i * 64;
      const int xw = ((cl & 3) * 2 + i) * 64;
      mbar_expect_tx(b + 48, 2 * HTILE);
      tma_col(sb + OFF_X + i * X_BYTES, &map_col, y0 - 1, xw - 1, b + 48);
      tma_col(sb + OFF_X + i * X_BYTES + HTILE, &map_col, y0 - 1, xw + 64, b + 48);
      mbar_expect_tx(b + 0, CSLOT);
      tma_row(sb + OFF_C + i * 2 * CSLOT, &map_row, (y0 - 1) * 32 + (xw >> 4), b + 0);
      mbar_expect_tx(b + 8, CSLOT);
      tma_row(sb + OFF_C + i * 2 * CSLOT + CSLOT, &map_row, y0 * 32 + (xw >> 4), b + 8);
      mbar_expect_tx(b + 16, XROW);
      mbar_expect_tx(b + 24, XROW);
    }
  }
  cluster_arrive();

  const unsigned char* pc = (const unsigned char*)p_coarse + 96 * rank;

  PRow hp[2][2], pA, pp;
  bool hv[2][2];
#pragma unroll
  for (int sd = 0; sd < 2; sd++)
#pragma unroll
    for (int h = 0; h < 2; h++) {
      const int hr = 16 * w + 8 * h + g, yy = y0 - 1 + hr, xx = sd ? x0 + 64 : x0 - 1;
      hv[sd][h] = hr < 34 && yy >= 0 && yy < IMG && xx >= 0 && xx < IMG;
      const unsigned char* a = pc + (hv[sd][h] ? ((size_t)(yy >> 1) * 256 + (xx >> 1)) * 192 : 0);
      hp[sd][h].a = ldg128(a + 16 * q);
      hp[sd][h].b = ldg64(a + 64 + 8 * q);
    }
  uint32_t poff = ((y0 >> 1) * 256 + (x0 >> 1) + 8 * w + g) * 192 + 16 * q;
  {
    const unsigned char* a = pc + poff - (y0 > 0 ? 49152 : 0);
    pA.a = ldg128(a);
    pA.b = ldg64(a + 64 - 8 * q);
    pp.a = ldg128(pc + poff);
    pp.b = ldg64(pc + poff + 64 - 8 * q);
    poff += 49152;
    asm volatile("prefetch.global.L2 [%0];" ::"l"(pc + poff + (q == 3 ? 16 : 16 * q)));
  }

  if (tid < 216) {
    const int dj = tid / 72, rem = tid % 72, kc = rem / 12, u = rem % 12;
    const unsigned char* src = (const unsigned char*)w_out + ((size_t)(dj * 96 + 48 * rank) * 96 + 8 * u) * 2;
    uint4 v[3][8];
#pragma unroll
    for (int kk = 0; kk < 8; kk++) {
      const int ci = cmap(kc, kk >> 1, kk & 1);
#pragma unroll
      for (int di = 0; di < 3; di++) v[di][kk] = ldg128(src + (size_t)di * 3 * 96 * 192 + ci * 192);
    }
    const uint32_t base = sb + OFF_U + dj * UT + kc * 1536 + (8 * (4 * (u >> 2)) + 2 * (u & 3)) * 16;
#pragma unroll
    for (int wd = 0; wd < 4; wd++) {
      uint32_t u0[2][4], u1[2][4], u2[2][4], u3[2][4];
#pragma unroll
      for (int kp = 0; kp < 4; kp++) {
        const uint32_t a0 = wsel(v[0][2 * kp], wd), a1 = wsel(v[0][2 * kp + 1], wd);
        const uint32_t b0 = wsel(v[1][2 * kp], wd), b1 = wsel(v[1][2 * kp + 1], wd);
        const uint32_t c0 = wsel(v[2][2 * kp], wd), c1 = wsel(v[2][2 * kp + 1], wd);
        u0[0][kp] = __byte_perm(a0, a1, 0x5410);
        u0[1][kp] = __byte_perm(a0, a1, 0x7632);
        u3[0][kp] = __byte_perm(c0, c1, 0x5410);
        u3[1][kp] = __byte_perm(c0, c1, 0x7632);
        const float s0l = bf_lo(a0) + bf_lo(c0), s1l = bf_lo(a1) + bf_lo(c1);
        const float s0h = bf_hi(a0) + bf_hi(c0), s1h = bf_hi(a1) + bf_hi(c1);
        u1[0][kp] = pack_bf16((s0l + bf_lo(b0)) * 0.5f, (s1l + bf_lo(b1)) * 0.5f);
        u1[1][kp] = pack_bf16((s0h + bf_hi(b0)) * 0.5f, (s1h + bf_hi(b1)) * 0.5f);
        u2[0][kp] = pack_bf16((s0l - bf_lo(b0)) * 0.5f, (s1l - bf_lo(b1)) * 0.5f);
        u2[1][kp] = pack_bf16((s0h - bf_hi(b0)) * 0.5f, (s1h - bf_hi(b1)) * 0.5f);
      }
#pragma unroll
      for (int e = 0; e < 2; e++) {
        const uint32_t a = base + (8 * wd + e) * 16;
        sts128(a, u0[e][0], u0[e][1], u0[e][2], u0[e][3]);
        sts128(a + 3 * UT, u1[e][0], u1[e][1], u1[e][2], u1[e][3]);
        sts128(a + 6 * UT, u2[e][0], u2[e][1], u2[e][2], u2[e][3]);
        sts128(a + 9 * UT, u3[e][0], u3[e][1], u3[e][2], u3[e][3]);
      }
    }
  } else {
    for (int blk = tid - 216; blk < 72; blk += 40) {
      const int kc = blk / 6, u = blk % 6;
      uint4 v[8];
#pragma unroll
      for (int kk = 0; kk < 8; kk++)
        v[kk] = ldg128((const unsigned char*)w_lat + ((size_t)(8 * kc + kk) * 96 + 48 * rank + 8 * u) * 2);
#pragma unroll
      for (int wd = 0; wd < 4; wd++) {
        const int n = u < 4 ? 8 * wd + 2 * u : 8 * (4 + (wd & 1)) + 2 * (2 * (u - 4) + (wd >> 1));
        const uint32_t a = sb + OFF_WL + kc * 768 + n * 16;
        uint32_t lo[4], hi[4];
#pragma unroll
        for (int kp = 0; kp < 4; kp++) {
          lo[kp] = __byte_perm(wsel(v[2 * kp], wd), wsel(v[2 * kp + 1], wd), 0x5410);
          hi[kp] = __byte_perm(wsel(v[2 * kp], wd), wsel(v[2 * kp + 1], wd), 0x7632);
        }
        sts128(a, lo[0], lo[1], lo[2], lo[3]);
        sts128(a + 16, hi[0], hi[1], hi[2], hi[3]);
      }
    }
  }
  fence_async_smem();
  __syncthreads();
  cluster_wait();

  const uint32_t bb = sb + OFF_BAR + wg * 64;
  const uint32_t dwl = make_desc(sb + OFF_WL, 768);
  const uint32_t dB = make_desc(sb + OFF_U, 1536);
  const uint32_t cs = sb + OFF_C + wg * 2 * CSLOT;
  const uint32_t dC = make_desc(cs, 16);
  const uint32_t xbase = sb + OFF_X + wg * X_BYTES;
  const uint32_t dH = make_desc(xbase, 16);
  const uint32_t hb = sb + OFF_H + wg * H_BYTES;
  const uint32_t eb = sb + OFF_E + wg * E_BYTES;
  const uint32_t xa = xbase + t128 * 16;
  const uint32_t peer = rank ^ 1;
  const uint32_t rdelta = __shfl_sync(0xffffffffu, mapa(bb, peer) - bb, 0);
#define r_xa (xa + rdelta)
#define r_bb (bb + rdelta)
  const int grp0 = (y0 - 1) * 32 + (x0 >> 4);
  const bool last_block = (y0 + 32 == IMG);

  const uint32_t e0 = g == 0, e7 = g == 7;
  const bool halo_lane = (w == 0 && g == 0) || (w == 3 && g == 7);
  const uint32_t ewr = eb + w * 256 + (e7 ? 128 : 0) + 32 * q;
  uint32_t erd = (halo_lane ? (e0 ? hb : hb + HSIDE) : (e0 ? eb + (w - 1) * 256 + 128 : eb + (w + 1) * 256)) + 32 * q;
  const uint32_t edelta = halo_lane ? 128 : EPAR;
  const uint32_t eadv = halo_lane ? 256 : 0;

  float ax[48], ay[48], lat[24];
  DRow D0, D1, D2, D3;
  uint32_t k0[12], k1[12];
  uint32_t fr0[12], fr1[12];

  auto d_finish = [&](auto ODD, DRow& d, const float(&acc)[24], const PRow& p, bool zero, int inext) {
    constexpr int odd = decltype(ODD)::value;
#pragma unroll
    for (int j = 0; j < 6; j++) {
      d.o0[j] = hadd2(pack_bf16(acc[4 * j], acc[4 * j + 1]), pw(p, j));
      d.o1[j] = hadd2(pack_bf16(acc[4 * j + 2], acc[4 * j + 3]), pw(p, j));
    }
    if (zero) {
#pragma unroll
      for (int j = 0; j < 6; j++) d.o0[j] = d.o1[j] = 0;
    }
    uint32_t ev[6];
#pragma unroll
    for (int j = 0; j < 6; j++) ev[j] = e0 ? d.o0[j] : d.o1[j];
    sts24_pred(ewr + odd * EPAR, ev, e0 | e7);
#pragma unroll
    for (int j = 0; j < 6; j++) {
      d.nA[j] = __shfl_up_sync(0xffffffffu, d.o1[j], 4);
      d.nB[j] = __shfl_down_sync(0xffffffffu, d.o0[j], 4);
    }
    bar_wg(1 + wg);
    if (t128 == 0 && inext <= 33) {
      mbar_expect_tx(bb + odd * 8, CSLOT);
      tma_row(cs + odd * CSLOT, &map_row, grp0 + inext * 32, bb + odd * 8);
    }
    const uint32_t ra = odd ? erd + edelta : erd;
    lds24_pred(ra, d.nA, e0);
    lds24_pred(ra, d.nB, e7);
    if (odd) erd += eadv;
  };
  auto send = [&](const float(&acc)[48], uint32_t(&k)[12], int b, uint32_t parity, bool go) {
    uint32_t sd[12];
#pragma unroll
    for (int j = 0; j < 12; j++) {
      const uint32_t lo = pack_bf16(acc[4 * j], acc[4 * j + 1]), hi = pack_bf16(acc[4 * j + 2], acc[4 * j + 3]);
      k[j] = rank ? hi : lo;
      sd[j] = rank ? lo : hi;
    }
    if (go) {
      mbar_wait(bb + 32 + 8 * b, parity);
#pragma unroll
      for (int J = 0; J < 3; J++)
        st_async128(r_xa + b * XROW + J * 2048, sd[4 * J], sd[4 * J + 1], sd[4 * J + 2], sd[4 * J + 3],
                    r_bb + 16 + 8 * b);
    }
  };
  uint32_t ooff = ((y0 * IMG) + x0 + 16 * w + 2 * g + rank) * 192 + 16 * q;
  auto finalize = [&](const uint32_t(&k)[12], int b, uint32_t parity) {
    mbar_wait(bb + 16 + 8 * b, parity);
    if (t128 == 0) mbar_expect_tx(bb + 16 + 8 * b, XROW);
#pragma unroll
    for (int J = 0; J < 3; J++) {
      const uint4 r = lds128(xa + b * XROW + J * 2048);
      uint4 o;
      o.x = hadd2(k[4 * J], r.x);
      o.y = hadd2(k[4 * J + 1], r.y);
      o.z = hadd2(k[4 * J + 2], r.z);
      o.w = hadd2(k[4 * J + 3], r.w);
      *(uint4*)((unsigned char*)out + (ooff - b * 98304 + 64 * J)) = o;
    }
    __syncwarp();
    if (lane == 0) mbar_arrive_remote(r_bb + 32 + 8 * b);
  };

  {
    float lat2[24];
    mbar_wait(bb + 48, 0);
    lateral<2560>(lat, dH, dwl);
    lateral<2560>(lat2, dH + (HTILE >> 4), dwl);
    wg_wait<0>();
    fence_regs(lat);
    fence_regs(lat2);
    __syncwarp();
    if (lane == 0) {
      mbar_arrive_remote(r_bb + 32);
      mbar_arrive_remote(r_bb + 40);
    }
#pragma unroll
    for (int h = 0; h < 2; h++) {
      const int hr = 16 * w + 8 * h + g;
      uint32_t v0[6], v1[6];
#pragma unroll
      for (int j = 0; j < 6; j++) {
        v0[j] = hv[0][h] ? hadd2(pack_bf16(lat[4 * j + 2 * h], lat[4 * j + 2 * h + 1]), pw(hp[0][h], j)) : 0u;
        v1[j] = hv[1][h] ? hadd2(pack_bf16(lat2[4 * j + 2 * h], lat2[4 * j + 2 * h + 1]), pw(hp[1][h], j)) : 0u;
      }
      sts24_pred(hb + hr * 128 + 32 * q, v0, hr < 34);
      sts24_pred(hb + HSIDE + hr * 128 + 32 * q, v1, hr < 34);
    }
    mbar_wait(bb + 0, 0);
    lateral<4096>(lat, dC, dwl);
    mbar_wait(bb + 8, 0);
    lateral<4096>(lat2, dC + (CSLOT >> 4), dwl);
    wg_wait<0>();
    fence_regs(lat);
    fence_regs(lat2);
    d_finish(IC<0>{}, D0, lat, pA, y0 == 0, 2);
    d_finish(IC<1>{}, D1, lat2, pp, false, 3);
    mbar_wait(bb + 0, 1);
    lateral<4096>(lat, dC, dwl);
    wg_wait<0>();
    fence_regs(lat);
    d_finish(IC<0>{}, D2, lat, pp, false, 4);
    frags<true>(fr0, D1, D2, 0);
    conv_group<true>(ax, fr0, dB, 1, 0);
#pragma unroll
    for (int i = 0; i < 48; i++) ay[i] = 0.f;
  }

  auto step = [&](auto PARC, DRow& d0, DRow& d1, DRow& d2, DRow& d3, int s) {
    constexpr uint32_t PAR = decltype(PARC)::value;
    const bool notfirst = PAR ? true : s > 0;
    const bool notlast = PAR ? s < NSTEP - 1 : true;
    wg_wait<1>();
    fence_regs(ay);
    send(ay, k1, 1, PAR ^ 1, notfirst);
    frags<false>(fr1, d2, d1, 0);
    conv_group<true>(ay, fr1, dB, 2, 0);
    wg_wait<1>();
    frags<true>(fr0, d1, d2, 1);
    conv_group<false>(ax, fr0, dB, 1, 1);
    wg_wait<1>();
    frags<false>(fr1, d2, d1, 1);
    conv_group<false>(ay, fr1, dB, 2, 1);
    if (notfirst) finalize(k1, 1, PAR ^ 1);
    wg_wait<1>();
    frags<true>(fr0, d1, d2, 2);
    conv_group<false>(ax, fr0, dB, 1, 2);
    wg_wait<1>();
    frags<false>(fr1, d2, d1, 2);
    conv_group<false>(ay, fr1, dB, 2, 2);
    pp.a = ldg128(pc + poff);
    pp.b = ldg64(pc + poff + 64 - 8 * q);
    wg_wait<1>();
    frags<false>(fr0, d0, d2, 0);
    wg_wait<0>();
    fence_regs(ax);
    fence_regs(ay);
#pragma unroll
    for (int i = 0; i < 48; i++) {
      asm volatile("add.f32 %0, %0, %1;\n\tfma.rn.f32 %1, %1, 0fC0000000, %0;" : "+f"(ax[i]), "+f"(ay[i]));
    }
    fence_regs(ax);
    fence_regs(ay);
    conv_group<false>(ax, fr0, dB, 0, 0);
    frags<false>(fr1, d0, d2, 1);
    conv_group<false>(ax, fr1, dB, 0, 1);
    mbar_wait(bb + 8, PAR ^ 1);
    lateral<4096>(lat, dC + (CSLOT >> 4), dwl);
    wg_wait<2>();
    frags<false>(fr0, d0, d2, 2);
    conv_group<false>(ax, fr0, dB, 0, 2);
    wg_wait<1>();
    fence_regs(lat);
    d_finish(IC<1>{}, d3, lat, pp, last_block && !notlast, 2 * s + 5);
    frags<false>(fr1, d3, d1, 0);
    conv_group<false>(ay, fr1, dB, 3, 0);
    wg_wait<1>();
    fence_regs(ax);
    frags<false>(fr0, d3, d1, 1);
    conv_group<false>(ay, fr0, dB, 3, 1);
    send(ax, k0, 0, PAR, true);
    if (notlast) mbar_wait(bb + 0, PAR);
    lateral<4096>(lat, dC, dwl);
    wg_wait<2>();
    frags<false>(fr1, d3, d1, 2);
    conv_group<false>(ay, fr1, dB, 3, 2);
    wg_wait<1>();
    fence_regs(lat);
    d_finish(IC<0>{}, d0, lat, pp, false, 2 * s + 6);
    if ((y0 >> 1) + s + 2 < 256) poff += 49152;
    asm volatile("prefetch.global.L2 [%0];" ::"l"(pc + poff + (q == 3 ? 16 : 16 * q)));
    frags<true>(fr0, d3, d0, 0);
    conv_group<true>(ax, fr0, dB, 1, 0);
    finalize(k0, 0, PAR);
    ooff += 2 * 98304;
  };

#pragma unroll 1
  for (int s = 0; s < NSTEP; s += 2) {
    step(IC<0>{}, D0, D1, D2, D3, s);
    step(IC<1>{}, D2, D3, D0, D1, s + 1);
  }
  wg_wait<0>();
  fence_regs(ax);
  fence_regs(ay);
  send(ay, k1, 1, 1, true);
  finalize(k1, 1, 1);
  cluster_arrive();
  cluster_wait();
}

typedef CUresult (*EncodeFn)(CUtensorMap*, CUtensorMapDataType, cuuint32_t, void*, const cuuint64_t*, const cuuint64_t*,
                             const cuuint32_t*, const cuuint32_t*, CUtensorMapInterleave, CUtensorMapSwizzle,
                             CUtensorMapL2promotion, CUtensorMapFloatOOBfill);

}

extern "C" void kernel_launch(void* const* d_in, const int* in_sizes, int n_in, void* d_out, int out_size) {
  (void)in_sizes;
  (void)n_in;
  (void)out_size;
  static EncodeFn encode = nullptr;
  if (!encode) {
    cudaFuncSetAttribute(fpn_kernel, cudaFuncAttributeMaxDynamicSharedMemorySize, SMEM_BYTES);
    void* fn = nullptr;
    cudaDriverEntryPointQueryResult st;
    cudaGetDriverEntryPoint("cuTensorMapEncodeTiled", &fn, cudaEnableDefault, &st);
    encode = (EncodeFn)fn;
  }
  CUtensorMap map_row, map_col;
  {
    const cuuint64_t dim[5] = {32, 8, 2, 16384, 3};
    const cuuint64_t str[4] = {384, 192, 3072, 64};
    const cuuint32_t box[5] = {32, 8, 2, 4, 3};
    const cuuint32_t es[5] = {1, 1, 1, 1, 1};
    encode(&map_row, CU_TENSOR_MAP_DATA_TYPE_BFLOAT16, 5, d_in[0], dim, str, box, es, CU_TENSOR_MAP_INTERLEAVE_NONE,
           CU_TENSOR_MAP_SWIZZLE_64B, CU_TENSOR_MAP_L2_PROMOTION_L2_256B, CU_TENSOR_MAP_FLOAT_OOB_FILL_NONE);
  }
  {
    const cuuint64_t dim[4] = {32, 512, 3, 512};
    const cuuint64_t str[3] = {98304, 64, 192};
    const cuuint32_t box[4] = {32, 40, 3, 1};
    const cuuint32_t es[4] = {1, 1, 1, 1};
    encode(&map_col, CU_TENSOR_MAP_DATA_TYPE_BFLOAT16, 4, d_in[0], dim, str, box, es, CU_TENSOR_MAP_INTERLEAVE_NONE,
           CU_TENSOR_MAP_SWIZZLE_64B, CU_TENSOR_MAP_L2_PROMOTION_L2_128B, CU_TENSOR_MAP_FLOAT_OOB_FILL_NONE);
  }
  fpn_kernel<<<128, 256, SMEM_BYTES, cudaStreamPerThread>>>(map_row, map_col, (const __nv_bfloat16*)d_in[1],
                                                            (const __nv_bfloat16*)d_in[2], (const __nv_bfloat16*)d_in[3],
                                                            (__nv_bfloat16*)d_out);
}
```

```cpp
#include <cuda_runtime.h>
#include <cuda.h>
#include <cuda_bf16.h>
#include <stdint.h>

namespace {

constexpr int IMG = 512;
constexpr int CSLOT = 12288;
constexpr int UT = 9216;
constexpr int OFF_C = 0;
constexpr int OFF_U = 4 * CSLOT;
constexpr int OFF_WL = OFF_U + 12 * UT;
constexpr int OFF_X = OFF_WL + 9216;
constexpr int XROW = 6144;
constexpr int HTILE = 7680;
constexpr int X_BYTES = 2 * HTILE;
constexpr int OFF_H = OFF_X + 2 * X_BYTES;
constexpr int HSIDE = 35 * 128;
constexpr int H_BYTES = 2 * HSIDE;
constexpr int OFF_E = OFF_H + 2 * H_BYTES;
constexpr int E_BYTES = 4096;
constexpr int OFF_BAR = OFF_E + 2 * E_BYTES;
constexpr int SMEM_BYTES = OFF_BAR + 128;
constexpr int NSTEP = 16;

#define R4(c, a, o) c(a[o]), c(a[o + 1]), c(a[o + 2]), c(a[o + 3])
#define R8(c, a, o) R4(c, a, o), R4(c, a, o + 4)
#define R24(c, a, o) R8(c, a, o), R8(c, a, o + 8), R8(c, a, o + 16)
#define RL24 \
  "%0, %1, %2, %3, %4, %5, %6, %7, %8, %9, %10, %11, %12, %13, %14, %15, %16, %17, %18, %19, %20, %21, %22, %23"
#define RL48                                                                                                       \
  RL24 ", %24, %25, %26, %27, %28, %29, %30, %31, %32, %33, %34, %35, %36, %37, %38, %39, %40, %41, %42, %43, %44, " \
       "%45, %46, %47"

constexpr uint32_t HI_W = 128 >> 4;
constexpr uint32_t HI_C = (512 >> 4) | (2u << 30);
template <int INIT>
__device__ __forceinline__ void wgmma_rs_n96(float (&d)[48], uint32_t a0, uint32_t a1, uint32_t a2, uint32_t a3,
                                             uint32_t db) {
  if constexpr (INIT == 1) {
    asm volatile(
        "{\n.reg .pred p;\n.reg .b64 db;\nsetp.ne.b32 p, 0, 0;\nmov.b64 db, {%52, %53};\n"
        "wgmma.mma_async.sync.aligned.m64n96k16.f32.bf16.bf16 {" RL48 "}, {%48, %49, %50, %51}, db, p, 1, 1, 0;\n}\n"
        : R24("=f", d, 0), R24("=f", d, 24)
        : "r"(a0), "r"(a1), "r"(a2), "r"(a3), "r"(db), "n"(HI_W));
  } else {
    asm volatile(
        "{\n.reg .pred p;\n.reg .b64 db;\nsetp.eq.b32 p, %54, 0;\nmov.b64 db, {%52, %53};\n"
        "wgmma.mma_async.sync.aligned.m64n96k16.f32.bf16.bf16 {" RL48 "}, {%48, %49, %50, %51}, db, p, 1, 1, 0;\n}\n"
        : R24("+f", d, 0), R24("+f", d, 24)
        : "r"(a0), "r"(a1), "r"(a2), "r"(a3), "r"(db), "n"(HI_W), "n"(INIT));
  }
}
template <int INIT>
__device__ __forceinline__ void wgmma_ss_n48(float (&d)[24], uint32_t da, uint32_t db) {
  if constexpr (INIT == 1) {
    asm volatile(
        "{\n.reg .pred p;\n.reg .b64 da, db;\nsetp.ne.b32 p, 0, 0;\nmov.b64 da, {%24, %26};\nmov.b64 db, {%25, %27};\n"
        "wgmma.mma_async.sync.aligned.m64n48k16.f32.bf16.bf16 {" RL24 "}, da, db, p, 1, 1, 0, 0;\n}\n"
        : R24("=f", d, 0)
        : "r"(da), "r"(db), "n"(HI_C), "n"(HI_W));
  } else {
    asm volatile(
        "{\n.reg .pred p;\n.reg .b64 da, db;\nsetp.eq.b32 p, %28, 0;\nmov.b64 da, {%24, %26};\nmov.b64 db, {%25, %27};\n"
        "wgmma.mma_async.sync.aligned.m64n48k16.f32.bf16.bf16 {" RL24 "}, da, db, p, 1, 1, 0, 0;\n}\n"
        : R24("+f", d, 0)
        : "r"(da), "r"(db), "n"(HI_C), "n"(HI_W), "n"(INIT));
  }
}
__device__ __forceinline__ void wg_fence() { asm volatile("wgmma.fence.sync.aligned;" ::: "memory"); }
__device__ __forceinline__ void wg_commit() { asm volatile("wgmma.commit_group.sync.aligned;" ::: "memory"); }
template <int N>
__device__ __forceinline__ void wg_wait() {
  asm volatile("wgmma.wait_group.sync.aligned %0;" ::"n"(N) : "memory");
}
template <int N>
__device__ __forceinline__ void fence_regs(float (&a)[N]) {
#pragma unroll
  for (int i = 0; i < N; i++) asm volatile("" : "+f"(a[i])::"memory");
}
constexpr uint32_t SB0 = 0x400;
__host__ __device__ constexpr uint32_t make_desc(uint32_t saddr, uint32_t lbo) {
  return ((saddr & 0x3FFFF) >> 4) | ((lbo >> 4) << 16);
}
__device__ __forceinline__ void fence_async_smem() { asm volatile("fence.proxy.async.shared::cta;" ::: "memory"); }
__device__ __forceinline__ void bar_wg(int id) { asm volatile("bar.sync %0, 128;" ::"r"(id) : "memory"); }

__device__ __forceinline__ uint32_t pack_bf16(float lo, float hi) {
  uint32_t r;
  asm("cvt.rn.bf16x2.f32 %0, %1, %2;" : "=r"(r) : "f"(hi), "f"(lo));
  return r;
}
__device__ __forceinline__ uint32_t hadd2(uint32_t a, uint32_t b) {
  uint32_t r;
  asm("add.rn.bf16x2 %0, %1, %2;" : "=r"(r) : "r"(a), "r"(b));
  return r;
}
__device__ __forceinline__ uint32_t hsub2(uint32_t a, uint32_t b) {
  uint32_t r;
  asm("sub.rn.bf16x2 %0, %1, %2;" : "=r"(r) : "r"(a), "r"(b));
  return r;
}
__device__ __forceinline__ float bf_lo(uint32_t a) { return __uint_as_float(a << 16); }
__device__ __forceinline__ float bf_hi(uint32_t a) { return __uint_as_float(a & 0xffff0000u); }

__device__ __forceinline__ uint4 ldg128(const void* p) {
  uint4 v;
  asm volatile("ld.global.nc.L1::no_allocate.v4.u32 {%0,%1,%2,%3}, [%4];"
               : "=r"(v.x), "=r"(v.y), "=r"(v.z), "=r"(v.w)
               : "l"(p));
  return v;
}
__device__ __forceinline__ uint2 ldg64(const void* p) {
  uint2 v;
  asm volatile("ld.global.nc.L1::no_allocate.v2.u32 {%0,%1}, [%2];" : "=r"(v.x), "=r"(v.y) : "l"(p));
  return v;
}
__device__ __forceinline__ void sts128(uint32_t a, uint32_t x, uint32_t y, uint32_t z, uint32_t w) {
  asm volatile("st.shared.v4.u32 [%0], {%1,%2,%3,%4};" ::"r"(a), "r"(x), "r"(y), "r"(z), "r"(w) : "memory");
}
__device__ __forceinline__ void sts24_pred(uint32_t a, const uint32_t (&v)[6], uint32_t pred) {
  asm volatile(
      "{\n.reg .pred p;\nsetp.ne.b32 p, %7, 0;\n"
      "@p st.shared.v4.u32 [%0], {%1,%2,%3,%4};\n"
      "@p st.shared.v2.u32 [%0+16], {%5,%6};\n}\n" ::"r"(a),
      "r"(v[0]), "r"(v[1]), "r"(v[2]), "r"(v[3]), "r"(v[4]), "r"(v[5]), "r"(pred)
      : "memory");
}
__device__ __forceinline__ uint4 lds128(uint32_t a) {
  uint4 v;
  asm volatile("ld.shared.v4.u32 {%0,%1,%2,%3}, [%4];" : "=r"(v.x), "=r"(v.y), "=r"(v.z), "=r"(v.w) : "r"(a) : "memory");
  return v;
}
__device__ __forceinline__ uint2 lds64(uint32_t a) {
  uint2 v;
  asm volatile("ld.shared.v2.u32 {%0,%1}, [%2];" : "=r"(v.x), "=r"(v.y) : "r"(a) : "memory");
  return v;
}
__device__ __forceinline__ void mbar_init(uint32_t bar, uint32_t cnt) {
  asm volatile("mbarrier.init.shared::cta.b64 [%0], %1;" ::"r"(bar), "r"(cnt) : "memory");
}
__device__ __forceinline__ void mbar_expect_tx(uint32_t bar, uint32_t bytes) {
  asm volatile("mbarrier.arrive.expect_tx.shared::cta.b64 _, [%0], %1;" ::"r"(bar), "r"(bytes) : "memory");
}
__device__ __forceinline__ void mbar_wait(uint32_t bar, uint32_t parity) {
  uint32_t ok;
  int it = 0;
  do {
    asm volatile(
        "{\n.reg .pred p;\n"
        "mbarrier.try_wait.parity.shared::cta.b64 p, [%1], %2;\n"
        "selp.u32 %0, 1, 0, p;\n}\n"
        : "=r"(ok)
        : "r"(bar), "r"(parity)
        : "memory");
    if (++it > (1 << 22)) __trap();
  } while (!ok);
}
__device__ __forceinline__ void mbar_arrive_remote(uint32_t rbar) {
  asm volatile("mbarrier.arrive.shared::cluster.b64 _, [%0];" ::"r"(rbar) : "memory");
}
__device__ __forceinline__ uint32_t mapa(uint32_t a, uint32_t rank) {
  uint32_t r;
  asm("mapa.shared::cluster.u32 %0, %1, %2;" : "=r"(r) : "r"(a), "r"(rank));
  return r;
}
__device__ __forceinline__ void st_async128(uint32_t ra, uint32_t x, uint32_t y, uint32_t z, uint32_t w, uint32_t rbar) {
  asm volatile("st.async.weak.shared::cluster.mbarrier::complete_tx::bytes.v4.b32 [%0], {%1,%2,%3,%4}, [%5];" ::"r"(ra),
               "r"(x), "r"(y), "r"(z), "r"(w), "r"(rbar)
               : "memory");
}
__device__ __forceinline__ void tma_row(uint32_t dst, const CUtensorMap* map, int grp, uint32_t bar) {
  asm volatile(
      "cp.async.bulk.tensor.5d.shared::cluster.global.mbarrier::complete_tx::bytes [%0], [%1, {%3, %3, %3, %4, %3}], "
      "[%2];" ::"r"(dst),
      "l"(map), "r"(bar), "r"(0), "r"(grp)
      : "memory");
}
__device__ __forceinline__ void tma_col(uint32_t dst, const CUtensorMap* map, int y, int x, uint32_t bar) {
  asm volatile(
      "cp.async.bulk.tensor.4d.shared::cluster.global.mbarrier::complete_tx::bytes [%0], [%1, {%3, %4, %3, %5}], "
      "[%2];" ::"r"(dst),
      "l"(map), "r"(bar), "r"(0), "r"(y), "r"(x)
      : "memory");
}
__device__ __forceinline__ void cluster_arrive() { asm volatile("barrier.cluster.arrive.release.aligned;" ::: "memory"); }
__device__ __forceinline__ void cluster_wait() { asm volatile("barrier.cluster.wait.acquire.aligned;" ::: "memory"); }

__device__ __forceinline__ uint32_t wsel(const uint4& v, int i) { return i == 0 ? v.x : i == 1 ? v.y : i == 2 ? v.z : v.w; }
__device__ __forceinline__ int cmap(int j, int q, int e) { return j < 4 ? 8 * q + 2 * j + e : 32 + 4 * q + 2 * (j - 4) + e; }

struct DRow {
  uint32_t o0[6], o1[6];
};
struct PRow {
  uint4 a;
  uint2 b;
};
__device__ __forceinline__ uint32_t pw(const PRow& p, int j) {
  return j == 0 ? p.a.x : j == 1 ? p.a.y : j == 2 ? p.a.z : j == 3 ? p.a.w : j == 4 ? p.b.x : p.b.y;
}
template <bool ADD>
__device__ __forceinline__ uint32_t top(uint32_t a, uint32_t b) {
  return ADD ? hadd2(a, b) : hsub2(a, b);
}
template <bool ADD>
__device__ __forceinline__ void edges(uint32_t (&te)[6], uint32_t ra, uint32_t rb) {
  const uint4 a = lds128(ra), b = lds128(rb);
  const uint2 c = lds64(ra + 16), d = lds64(rb + 16);
  te[0] = top<ADD>(a.x, b.x);
  te[1] = top<ADD>(a.y, b.y);
  te[2] = top<ADD>(a.z, b.z);
  te[3] = top<ADD>(a.w, b.w);
  te[4] = top<ADD>(c.x, d.x);
  te[5] = top<ADD>(c.y, d.y);
}
template <bool ADD>
__device__ __forceinline__ void frags(uint32_t (&f)[12], const DRow& a, const DRow& b, const uint32_t (&te)[6], int ks,
                                      bool e0, bool e7) {
#pragma unroll
  for (int i = 0; i < 2; i++) {
    const int j = 2 * ks + i;
    const uint32_t t0 = top<ADD>(a.o0[j], b.o0[j]), t1 = top<ADD>(a.o1[j], b.o1[j]);
    const uint32_t nA = __shfl_up_sync(0xffffffffu, t1, 4);
    const uint32_t nB = __shfl_down_sync(0xffffffffu, t0, 4);
    f[0 + 2 * i] = e0 ? te[j] : nA;
    f[1 + 2 * i] = t0;
    f[4 + 2 * i] = t0;
    f[5 + 2 * i] = t1;
    f[8 + 2 * i] = t1;
    f[9 + 2 * i] = e7 ? te[j] : nB;
  }
}
__device__ __forceinline__ void fragt(uint32_t (&f)[12], const DRow& t, const uint32_t (&te)[6], int ks, bool e0,
                                      bool e7) {
#pragma unroll
  for (int i = 0; i < 2; i++) {
    const int j = 2 * ks + i;
    const uint32_t t0 = t.o0[j], t1 = t.o1[j];
    const uint32_t nA = __shfl_up_sync(0xffffffffu, t1, 4);
    const uint32_t nB = __shfl_down_sync(0xffffffffu, t0, 4);
    f[0 + 2 * i] = e0 ? te[j] : nA;
    f[1 + 2 * i] = t0;
    f[4 + 2 * i] = t0;
    f[5 + 2 * i] = t1;
    f[8 + 2 * i] = t1;
    f[9 + 2 * i] = e7 ? te[j] : nB;
  }
}
template <int INIT>
__device__ __forceinline__ void conv_group(float (&acc)[48], const uint32_t (&f)[12], uint32_t dB, int pos, int ks) {
  wg_fence();
  wgmma_rs_n96<INIT>(acc, f[0], f[1], f[2], f[3], dB + (uint32_t)(((3 * pos + 0) * UT + 2 * ks * 1536) >> 4));
  wgmma_rs_n96<0>(acc, f[4], f[5], f[6], f[7], dB + (uint32_t)(((3 * pos + 1) * UT + 2 * ks * 1536) >> 4));
  wgmma_rs_n96<0>(acc, f[8], f[9], f[10], f[11], dB + (uint32_t)(((3 * pos + 2) * UT + 2 * ks * 1536) >> 4));
  wg_commit();
}
template <int CH, int INIT>
__device__ __forceinline__ void lateral(float (&acc)[24], uint32_t dA, uint32_t dwl) {
  wg_fence();
#pragma unroll
  for (int k = 0; k < 6; k++) {
    const uint32_t a = dA + (uint32_t)(((k >> 1) * CH + (k & 1) * 32) >> 4);
    const uint32_t b = dwl + (uint32_t)(k * 1536 >> 4);
    if (k == 0)
      wgmma_ss_n48<INIT>(acc, a, b);
    else
      wgmma_ss_n48<0>(acc, a, b);
  }
  wg_commit();
}

#define AI __attribute__((always_inline))
template <int V>
struct IC {
  static constexpr int value = V;
};

template <int RANK>
__device__ __forceinline__ void fpn_body(const CUtensorMap& map_row, const CUtensorMap& map_col,
                                         const __nv_bfloat16* __restrict__ p_coarse,
                                         const __nv_bfloat16* __restrict__ w_lat,
                                         const __nv_bfloat16* __restrict__ w_out, __nv_bfloat16* __restrict__ out) {
  extern __shared__ __align__(1024) unsigned char smem[];
  const uint32_t sb = (uint32_t)__cvta_generic_to_shared(smem);
  if ((sb & 0xFFFFFFu) != SB0) __trap();
  const int tid = threadIdx.x;
  const int wg = __shfl_sync(0xffffffffu, tid >> 7, 0);
  const int t128 = tid & 127;
  const int w = __shfl_sync(0xffffffffu, (tid >> 5) & 3, 0);
  const int lane = tid & 31;
  const int g = lane >> 2, q = lane & 3;
  constexpr uint32_t rank = RANK;
  const int cl = blockIdx.x >> 1;
  const int y0 = (cl >> 2) * 32;
  const int x0 = ((cl & 3) * 2 + wg) * 64;

  if (tid == 0) {
#pragma unroll
    for (int i = 0; i < 2; i++) {
      const uint32_t b = sb + OFF_BAR + i * 64;
      mbar_init(b + 0, 1);
      mbar_init(b + 8, 1);
      mbar_init(b + 16, 1);
      mbar_init(b + 24, 1);
      mbar_init(b + 32, 4);
      mbar_init(b + 40, 4);
      mbar_init(b + 48, 1);
    }
    asm volatile("fence.mbarrier_init.release.cluster;" ::: "memory");
    fence_async_smem();
#pragma unroll
    for (int i = 0; i < 2; i++) {
      const uint32_t b = sb + OFF_BAR + i * 64;
      const int xw = ((cl & 3) * 2 + i) * 64;
      mbar_expect_tx(b + 48, 2 * HTILE);
      tma_col(sb + OFF_X + i * X_BYTES, &map_col, y0 - 1, xw - 1, b + 48);
      tma_col(sb + OFF_X + i * X_BYTES + HTILE, &map_col, y0 - 1, xw + 64, b + 48);
      mbar_expect_tx(b + 0, CSLOT);
      tma_row(sb + OFF_C + i * 2 * CSLOT, &map_row, (y0 - 1) * 32 + (xw >> 4), b + 0);
      mbar_expect_tx(b + 8, CSLOT);
      tma_row(sb + OFF_C + i * 2 * CSLOT + CSLOT, &map_row, y0 * 32 + (xw >> 4), b + 8);
      mbar_expect_tx(b + 16, XROW);
      mbar_expect_tx(b + 24, XROW);
    }
  }
  cluster_arrive();

  const unsigned char* pc = (const unsigned char*)p_coarse + 96 * rank;

  PRow hp[2][2], pA, pp;
  bool hv[2][2];
#pragma unroll
  for (int sd = 0; sd < 2; sd++)
#pragma unroll
    for (int h = 0; h < 2; h++) {
      const int hr = 16 * w + 8 * h + g, yy = y0 - 1 + hr, xx = sd ? x0 + 64 : x0 - 1;
      hv[sd][h] = hr < 34 && yy >= 0 && yy < IMG && xx >= 0 && xx < IMG;
      const unsigned char* a = pc + (hv[sd][h] ? ((size_t)(yy >> 1) * 256 + (xx >> 1)) * 192 : 0);
      hp[sd][h].a = ldg128(a + 16 * q);
      hp[sd][h].b = ldg64(a + 64 + 8 * q);
    }
  uint32_t poff = ((y0 >> 1) * 256 + (x0 >> 1) + 8 * w + g) * 192 + 16 * q;
  {
    const unsigned char* a = pc + poff - (y0 > 0 ? 49152 : 0);
    pA.a = ldg128(a);
    pA.b = ldg64(a + 64 - 8 * q);
    pp.a = ldg128(pc + poff);
    pp.b = ldg64(pc + poff + 64 - 8 * q);
    poff += 49152;
  }

  if (tid < 216) {
    const int dj = tid / 72, rem = tid % 72, kc = rem / 12, u = rem % 12;
    const unsigned char* src = (const unsigned char*)w_out + ((size_t)(dj * 96 + 48 * rank) * 96 + 8 * u) * 2;
    uint4 v[3][8];
#pragma unroll
    for (int kk = 0; kk < 8; kk++) {
      const int ci = cmap(kc, kk >> 1, kk & 1);
#pragma unroll
      for (int di = 0; di < 3; di++) v[di][kk] = ldg128(src + (size_t)di * 3 * 96 * 192 + ci * 192);
    }
    const uint32_t base = sb + OFF_U + dj * UT + kc * 1536 + (8 * (4 * (u >> 2)) + 2 * (u & 3)) * 16;
#pragma unroll
    for (int wd = 0; wd < 4; wd++) {
      uint32_t u0[2][4], u1[2][4], u2[2][4], u3[2][4];
#pragma unroll
      for (int kp = 0; kp < 4; kp++) {
        const uint32_t a0 = wsel(v[0][2 * kp], wd), a1 = wsel(v[0][2 * kp + 1], wd);
        const uint32_t b0 = wsel(v[1][2 * kp], wd), b1 = wsel(v[1][2 * kp + 1], wd);
        const uint32_t c0 = wsel(v[2][2 * kp], wd), c1 = wsel(v[2][2 * kp + 1], wd);
        u0[0][kp] = __byte_perm(a0, a1, 0x5410);
        u0[1][kp] = __byte_perm(a0, a1, 0x7632);
        u3[0][kp] = __byte_perm(c0, c1, 0x5410);
        u3[1][kp] = __byte_perm(c0, c1, 0x7632);
        const float s0l = bf_lo(a0) + bf_lo(c0), s1l = bf_lo(a1) + bf_lo(c1);
        const float s0h = bf_hi(a0) + bf_hi(c0), s1h = bf_hi(a1) + bf_hi(c1);
        u1[0][kp] = pack_bf16((s0l + bf_lo(b0)) * 0.5f, (s1l + bf_lo(b1)) * 0.5f);
        u1[1][kp] = pack_bf16((s0h + bf_hi(b0)) * 0.5f, (s1h + bf_hi(b1)) * 0.5f);
        u2[0][kp] = pack_bf16((s0l - bf_lo(b0)) * 0.5f, (s1l - bf_lo(b1)) * 0.5f);
        u2[1][kp] = pack_bf16((s0h - bf_hi(b0)) * 0.5f, (s1h - bf_hi(b1)) * 0.5f);
      }
#pragma unroll
      for (int e = 0; e < 2; e++) {
        const uint32_t a = base + (8 * wd + e) * 16;
        sts128(a, u0[e][0], u0[e][1], u0[e][2], u0[e][3]);
        sts128(a + 3 * UT, u1[e][0], u1[e][1], u1[e][2], u1[e][3]);
        sts128(a + 6 * UT, u2[e][0], u2[e][1], u2[e][2], u2[e][3]);
        sts128(a + 9 * UT, u3[e][0], u3[e][1], u3[e][2], u3[e][3]);
      }
    }
  } else {
    for (int blk = tid - 216; blk < 72; blk += 40) {
      const int kc = blk / 6, u = blk % 6;
      uint4 v[8];
#pragma unroll
      for (int kk = 0; kk < 8; kk++)
        v[kk] = ldg128((const unsigned char*)w_lat + ((size_t)(8 * kc + kk) * 96 + 48 * rank + 8 * u) * 2);
#pragma unroll
      for (int wd = 0; wd < 4; wd++) {
        const int n = u < 4 ? 8 * wd + 2 * u : 8 * (4 + (wd & 1)) + 2 * (2 * (u - 4) + (wd >> 1));
        const uint32_t a = sb + OFF_WL + kc * 768 + n * 16;
        uint32_t lo[4], hi[4];
#pragma unroll
        for (int kp = 0; kp < 4; kp++) {
          lo[kp] = __byte_perm(wsel(v[2 * kp], wd), wsel(v[2 * kp + 1], wd), 0x5410);
          hi[kp] = __byte_perm(wsel(v[2 * kp], wd), wsel(v[2 * kp + 1], wd), 0x7632);
        }
        sts128(a, lo[0], lo[1], lo[2], lo[3]);
        sts128(a + 16, hi[0], hi[1], hi[2], hi[3]);
      }
    }
  }
  fence_async_smem();
  __syncthreads();
  cluster_wait();

  const uint32_t bb = sb + OFF_BAR + wg * 64;
  constexpr uint32_t dwl = make_desc(SB0 + OFF_WL, 768);
  constexpr uint32_t dB = make_desc(SB0 + OFF_U, 1536);
  const uint32_t cs = sb + OFF_C + wg * 2 * CSLOT;
  const uint32_t dC = make_desc(SB0 + OFF_C, 16) + wg * (2 * CSLOT >> 4);
  const uint32_t xbase = sb + OFF_X + wg * X_BYTES;
  const uint32_t dH = make_desc(SB0 + OFF_X, 16) + wg * (X_BYTES >> 4);
  const uint32_t hb = sb + OFF_H + wg * H_BYTES;
  const uint32_t eb = sb + OFF_E + wg * E_BYTES;
  const uint32_t xa = xbase + t128 * 16;
  const uint32_t peer = rank ^ 1;
  const uint32_t rdelta = __shfl_sync(0xffffffffu, mapa(bb, peer) - bb, 0);
#define r_xa (xa + rdelta)
#define r_bb (bb + rdelta)
  const int grp0 = (y0 - 1) * 32 + (x0 >> 4);
  const bool last_block = (y0 + 32 == IMG);

  const bool e0 = g == 0, e7 = g == 7;
  const bool halo_lane = (w == 0 && g < 4) || (w == 3 && g >= 4);
  const uint32_t ewr = eb + (2 * w + (e7 ? 1 : 0)) * 512 + 32 * q;
  const uint32_t erd =
      (halo_lane ? (g < 4 ? hb : hb + HSIDE) : (g < 4 ? eb + (2 * w - 1) * 512 : eb + (2 * w + 2) * 512)) + 32 * q;
  const uint32_t emask = halo_lane ? 0xFFFFu : 511u;
  auto er = [&](int k) AI { return erd + (((uint32_t)k << 8) & emask); };

  float ax[48], ay[48], lat[24];
  DRow d1, d2, t0, t3;
  uint32_t f0[12], f1[12], f2[12], te[6], kp[12];

  auto d_finish = [&](auto MODE, int i, DRow& d, DRow& t, const float(&acc)[24], const PRow& p, bool zero) AI {
    constexpr int mode = decltype(MODE)::value;
    const int odd = i & 1;
#pragma unroll
    for (int j = 0; j < 6; j++) {
      uint32_t n0 = hadd2(pack_bf16(acc[4 * j], acc[4 * j + 1]), pw(p, j));
      uint32_t n1 = hadd2(pack_bf16(acc[4 * j + 2], acc[4 * j + 3]), pw(p, j));
      if (zero) n0 = n1 = 0;
      if (mode == 1) {
        t.o0[j] = hsub2(n0, d.o0[j]);
        t.o1[j] = hsub2(n1, d.o1[j]);
      }
      if (mode == 2) {
        t.o0[j] = hsub2(d.o0[j], n0);
        t.o1[j] = hsub2(d.o1[j], n1);
      }
      d.o0[j] = n0;
      d.o1[j] = n1;
    }
    uint32_t ev[6];
#pragma unroll
    for (int j = 0; j < 6; j++) ev[j] = e0 ? d.o0[j] : d.o1[j];
    sts24_pred(ewr + (i & 3) * 128, ev, e0 || e7);
    bar_wg(1 + wg);
    if (t128 == 0 && i + 2 <= 33) {
      mbar_expect_tx(bb + odd * 8, CSLOT);
      tma_row(cs + odd * CSLOT, &map_row, grp0 + (i + 2) * 32, bb + odd * 8);
    }
  };
  auto send = [&](const float(&acc)[48], int b, uint32_t parity) AI {
    constexpr int rk = RANK;
    mbar_wait(bb + 32 + 8 * b, parity);
#pragma unroll
    for (int J = 0; J < 3; J++) {
      uint32_t sd[4];
#pragma unroll
      for (int i = 0; i < 4; i++) {
        const int j = 4 * J + i;
        sd[i] = pack_bf16(acc[4 * j + 2 - 2 * rk], acc[4 * j + 3 - 2 * rk]);
        kp[j] = pack_bf16(acc[4 * j + 2 * rk], acc[4 * j + 2 * rk + 1]);
      }
      st_async128(r_xa + b * XROW + J * 2048, sd[0], sd[1], sd[2], sd[3], r_bb + 16 + 8 * b);
    }
  };
  uint32_t ooff = ((y0 * IMG) + x0 + 16 * w + 2 * g + rank) * 192 + 16 * q;
  auto finalize = [&](int b, uint32_t parity) AI {
    mbar_wait(bb + 16 + 8 * b, parity);
    if (t128 == 0) mbar_expect_tx(bb + 16 + 8 * b, XROW);
#pragma unroll
    for (int J = 0; J < 3; J++) {
      const uint4 r = lds128(xa + b * XROW + J * 2048);
      uint4 o;
      o.x = hadd2(kp[4 * J + 0], r.x);
      o.y = hadd2(kp[4 * J + 1], r.y);
      o.z = hadd2(kp[4 * J + 2], r.z);
      o.w = hadd2(kp[4 * J + 3], r.w);
      *(uint4*)((unsigned char*)out + (ooff + 64 * J)) = o;
    }
    ooff += 98304;
    __syncwarp();
    if (lane == 0) mbar_arrive_remote(r_bb + 32 + 8 * b);
  };

  {
    float lat2[24];
    mbar_wait(bb + 48, 0);
    lateral<2560, 1>(lat, dH, dwl);
    lateral<2560, 1>(lat2, dH + (HTILE >> 4), dwl);
    wg_wait<0>();
    fence_regs(lat);
    fence_regs(lat2);
    __syncwarp();
    if (lane == 0) {
      mbar_arrive_remote(r_bb + 32);
      mbar_arrive_remote(r_bb + 40);
    }
#pragma unroll
    for (int h = 0; h < 2; h++) {
      const int hr = 16 * w + 8 * h + g;
      uint32_t v0[6], v1[6];
#pragma unroll
      for (int j = 0; j < 6; j++) {
        v0[j] = hv[0][h] ? hadd2(pack_bf16(lat[4 * j + 2 * h], lat[4 * j + 2 * h + 1]), pw(hp[0][h], j)) : 0u;
        v1[j] = hv[1][h] ? hadd2(pack_bf16(lat2[4 * j + 2 * h], lat2[4 * j + 2 * h + 1]), pw(hp[1][h], j)) : 0u;
      }
      sts24_pred(hb + hr * 128 + 32 * q, v0, hr < 34);
      sts24_pred(hb + HSIDE + hr * 128 + 32 * q, v1, hr < 34);
    }
    mbar_wait(bb + 0, 0);
    lateral<4096, 1>(lat, dC, dwl);
    mbar_wait(bb + 8, 0);
    lateral<4096, 1>(lat2, dC + (CSLOT >> 4), dwl);
    wg_wait<0>();
    fence_regs(lat);
    fence_regs(lat2);
    d_finish(IC<0>{}, 0, d2, t0, lat, pA, y0 == 0);
    d_finish(IC<0>{}, 1, d1, t3, lat2, pp, false);
    mbar_wait(bb + 0, 1);
    lateral<4096, 1>(lat, dC, dwl);
    wg_wait<0>();
    fence_regs(lat);
    d_finish(IC<2>{}, 2, d2, t0, lat, pp, false);
    pp.a = ldg128(pc + poff);
    pp.b = ldg64(pc + poff + 64 - 8 * q);
    edges<true>(te, er(0) + 128, er(1));
    frags<true>(f0, d1, d2, te, 0, e0, e7);
    conv_group<1>(ax, f0, dB, 1, 0);
    frags<true>(f1, d1, d2, te, 1, e0, e7);
  }

  auto stepA = [&](auto FIRST, int s) AI {
    constexpr bool notfirst = !decltype(FIRST)::value;
    const uint32_t par = s & 1;
    wg_wait<1>();
    if (notfirst) fence_regs(ay);
    conv_group<0>(ax, f1, dB, 1, 1);
    frags<true>(f2, d1, d2, te, 2, e0, e7);
    edges<false>(te, er(s + 1), er(s) + 128);
    if (notfirst) finalize(0, par ^ 1);
    wg_wait<1>();
    conv_group<0>(ax, f2, dB, 1, 2);
    frags<false>(f0, d2, d1, te, 0, e0, e7);
    if (notfirst) send(ay, 1, par ^ 1);
    wg_wait<1>();
    conv_group<notfirst ? 2 : 1>(ay, f0, dB, 2, 0);
    frags<false>(f1, d2, d1, te, 1, e0, e7);
    wg_wait<1>();
    conv_group<0>(ay, f1, dB, 2, 1);
    frags<false>(f2, d2, d1, te, 2, e0, e7);
    edges<false>(te, er(s), er(s + 1));
    wg_wait<1>();
    conv_group<0>(ay, f2, dB, 2, 2);
    fragt(f0, t0, te, 0, e0, e7);
    if (notfirst) finalize(1, par ^ 1);
    mbar_wait(bb + 8, par ^ 1);
    wg_wait<1>();
    lateral<4096, 2>(lat, dC + (CSLOT >> 4), dwl);
    fragt(f1, t0, te, 1, e0, e7);
    wg_wait<1>();
    fence_regs(ax);
    fence_regs(ay);
  };
  auto stepB = [&](auto LAST, int s) AI {
    constexpr bool notlast = !decltype(LAST)::value;
    const uint32_t par = s & 1;
#pragma unroll
    for (int i = 0; i < 48; i++) {
      asm volatile("add.f32 %0, %0, %1;\n\tfma.rn.f32 %1, %1, 0fC0000000, %0;" : "+f"(ax[i]), "+f"(ay[i]));
    }
    fence_regs(ax);
    fence_regs(ay);
    conv_group<0>(ax, f0, dB, 0, 0);
    conv_group<0>(ax, f1, dB, 0, 1);
    fragt(f2, t0, te, 2, e0, e7);
    conv_group<0>(ax, f2, dB, 0, 2);
    wg_wait<3>();
    fence_regs(lat);
    d_finish(IC<1>{}, 2 * s + 3, d1, t3, lat, pp, last_block && !notlast);
    edges<false>(te, er(s + 1) + 128, er(s) + 128);
    if (notlast) mbar_wait(bb + 0, par);
    wg_wait<2>();
    if (notlast) lateral<4096, 2>(lat, dC, dwl);
    fragt(f0, t3, te, 0, e0, e7);
    wg_wait<notlast ? 2 : 1>();
    conv_group<0>(ay, f0, dB, 3, 0);
    fragt(f1, t3, te, 1, e0, e7);
    wg_wait<notlast ? 2 : 1>();
    fence_regs(ax);
    conv_group<0>(ay, f1, dB, 3, 1);
    fragt(f2, t3, te, 2, e0, e7);
    conv_group<0>(ay, f2, dB, 3, 2);
    send(ax, 0, par);
  };
  auto stepC = [&](int s) AI {
    wg_wait<2>();
    fence_regs(lat);
    d_finish(IC<2>{}, 2 * s + 4, d2, t0, lat, pp, false);
    if ((y0 >> 1) + s + 2 < 256) poff += 49152;
    pp.a = ldg128(pc + poff);
    pp.b = ldg64(pc + poff + 64 - 8 * q);
    edges<true>(te, er(s + 1) + 128, er(s + 2));
    frags<true>(f0, d1, d2, te, 0, e0, e7);
    wg_wait<1>();
    conv_group<2>(ax, f0, dB, 1, 0);
    frags<true>(f1, d1, d2, te, 1, e0, e7);
  };

  stepA(IC<1>{}, 0);
#pragma unroll 1
  for (int s = 0; s < NSTEP - 1; s++) {
    stepB(IC<0>{}, s);
    stepC(s);
    stepA(IC<0>{}, s + 1);
  }
  stepB(IC<1>{}, NSTEP - 1);
  finalize(0, 1);
  wg_wait<0>();
  fence_regs(ay);
  send(ay, 1, 1);
  finalize(1, 1);
  cluster_arrive();
  cluster_wait();
}

__global__ void __cluster_dims__(2, 1, 1) __launch_bounds__(256, 1)
    fpn_kernel(const __grid_constant__ CUtensorMap map_row, const __grid_constant__ CUtensorMap map_col,
               const __nv_bfloat16* __restrict__ p_coarse, const __nv_bfloat16* __restrict__ w_lat,
               const __nv_bfloat16* __restrict__ w_out, __nv_bfloat16* __restrict__ out) {
  uint32_t rank;
  asm("mov.u32 %0, %%cluster_ctarank;" : "=r"(rank));
  if (rank)
    fpn_body<1>(map_row, map_col, p_coarse, w_lat, w_out, out);
  else
    fpn_body<0>(map_row, map_col, p_coarse, w_lat, w_out, out);
}

typedef CUresult (*EncodeFn)(CUtensorMap*, CUtensorMapDataType, cuuint32_t, void*, const cuuint64_t*, const cuuint64_t*,
                             const cuuint32_t*, const cuuint32_t*, CUtensorMapInterleave, CUtensorMapSwizzle,
                             CUtensorMapL2promotion, CUtensorMapFloatOOBfill);

}

extern "C" void kernel_launch(void* const* d_in, const int* in_sizes, int n_in, void* d_out, int out_size) {
  (void)in_sizes;
  (void)n_in;
  (void)out_size;
  static EncodeFn encode = nullptr;
  if (!encode) {
    cudaFuncSetAttribute(fpn_kernel, cudaFuncAttributeMaxDynamicSharedMemorySize, SMEM_BYTES);
    void* fn = nullptr;
    cudaDriverEntryPointQueryResult st;
    cudaGetDriverEntryPoint("cuTensorMapEncodeTiled", &fn, cudaEnableDefault, &st);
    encode = (EncodeFn)fn;
  }
  CUtensorMap map_row, map_col;
  {
    const cuuint64_t dim[5] = {32, 8, 2, 16384, 3};
    const cuuint64_t str[4] = {384, 192, 3072, 64};
    const cuuint32_t box[5] = {32, 8, 2, 4, 3};
    const cuuint32_t es[5] = {1, 1, 1, 1, 1};
    encode(&map_row, CU_TENSOR_MAP_DATA_TYPE_BFLOAT16, 5, d_in[0], dim, str, box, es, CU_TENSOR_MAP_INTERLEAVE_NONE,
           CU_TENSOR_MAP_SWIZZLE_64B, CU_TENSOR_MAP_L2_PROMOTION_L2_256B, CU_TENSOR_MAP_FLOAT_OOB_FILL_NONE);
  }
  {
    const cuuint64_t dim[4] = {32, 512, 3, 512};
    const cuuint64_t str[3] = {98304, 64, 192};
    const cuuint32_t box[4] = {32, 40, 3, 1};
    const cuuint32_t es[4] = {1, 1, 1, 1};
    encode(&map_col, CU_TENSOR_MAP_DATA_TYPE_BFLOAT16, 4, d_in[0], dim, str, box, es, CU_TENSOR_MAP_INTERLEAVE_NONE,
           CU_TENSOR_MAP_SWIZZLE_64B, CU_TENSOR_MAP_L2_PROMOTION_L2_128B, CU_TENSOR_MAP_FLOAT_OOB_FILL_NONE);
  }
  fpn_kernel<<<128, 256, SMEM_BYTES, cudaStreamPerThread>>>(map_row, map_col, (const __nv_bfloat16*)d_in[1],
                                                            (const __nv_bfloat16*)d_in[2], (const __nv_bfloat16*)d_in[3],
                                                            (__nv_bfloat16*)d_out);
}
```

```cpp
#include <cuda_runtime.h>
#include <cuda.h>
#include <cuda_bf16.h>
#include <stdint.h>

namespace {

constexpr int IMG = 512;
constexpr int CSLOT = 12288;
constexpr int UT = 9216;
constexpr int OFF_C = 0;
constexpr int OFF_U = 4 * CSLOT;
constexpr int OFF_WL = OFF_U + 12 * UT;
constexpr int OFF_X = OFF_WL + 9216;
constexpr int XROW = 6144;
constexpr int HTILE = 7680;
constexpr int X_BYTES = 2 * HTILE;
constexpr int OFF_H = OFF_X + 2 * X_BYTES;
constexpr int HSIDE = 35 * 128;
constexpr int H_BYTES = 2 * HSIDE;
constexpr int OFF_E = OFF_H + 2 * H_BYTES;
constexpr int E_BYTES = 4096;
constexpr int OFF_BAR = OFF_E + 2 * E_BYTES;
constexpr int SMEM_BYTES = OFF_BAR + 128;
constexpr int NSTEP = 16;

#define R4(c, a, o) c(a[o]), c(a[o + 1]), c(a[o + 2]), c(a[o + 3])
#define R8(c, a, o) R4(c, a, o), R4(c, a, o + 4)
#define R24(c, a, o) R8(c, a, o), R8(c, a, o + 8), R8(c, a, o + 16)
#define RL24 \
  "%0, %1, %2, %3, %4, %5, %6, %7, %8, %9, %10, %11, %12, %13, %14, %15, %16, %17, %18, %19, %20, %21, %22, %23"
#define RL48                                                                                                       \
  RL24 ", %24, %25, %26, %27, %28, %29, %30, %31, %32, %33, %34, %35, %36, %37, %38, %39, %40, %41, %42, %43, %44, " \
       "%45, %46, %47"

constexpr uint32_t HI_W = 128 >> 4;
constexpr uint32_t HI_C = (512 >> 4) | (2u << 30);
template <int INIT>
__device__ __forceinline__ void wgmma_rs_n96(float (&d)[48], uint32_t a0, uint32_t a1, uint32_t a2, uint32_t a3,
                                             uint32_t db) {
  if constexpr (INIT == 1) {
    asm volatile(
        "{\n.reg .pred p;\n.reg .b64 db;\nsetp.ne.b32 p, 0, 0;\nmov.b64 db, {%52, %53};\n"
        "wgmma.mma_async.sync.aligned.m64n96k16.f32.bf16.bf16 {" RL48 "}, {%48, %49, %50, %51}, db, p, 1, 1, 0;\n}\n"
        : R24("=f", d, 0), R24("=f", d, 24)
        : "r"(a0), "r"(a1), "r"(a2), "r"(a3), "r"(db), "n"(HI_W));
  } else {
    asm volatile(
        "{\n.reg .pred p;\n.reg .b64 db;\nsetp.eq.b32 p, %54, 0;\nmov.b64 db, {%52, %53};\n"
        "wgmma.mma_async.sync.aligned.m64n96k16.f32.bf16.bf16 {" RL48 "}, {%48, %49, %50, %51}, db, p, 1, 1, 0;\n}\n"
        : R24("+f", d, 0), R24("+f", d, 24)
        : "r"(a0), "r"(a1), "r"(a2), "r"(a3), "r"(db), "n"(HI_W), "n"(INIT));
  }
}
template <int INIT>
__device__ __forceinline__ void wgmma_ss_n48(float (&d)[24], uint32_t da, uint32_t db) {
  if constexpr (INIT == 1) {
    asm volatile(
        "{\n.reg .pred p;\n.reg .b64 da, db;\nsetp.ne.b32 p, 0, 0;\nmov.b64 da, {%24, %26};\nmov.b64 db, {%25, %27};\n"
        "wgmma.mma_async.sync.aligned.m64n48k16.f32.bf16.bf16 {" RL24 "}, da, db, p, 1, 1, 0, 0;\n}\n"
        : R24("=f", d, 0)
        : "r"(da), "r"(db), "n"(HI_C), "n"(HI_W));
  } else {
    asm volatile(
        "{\n.reg .pred p;\n.reg .b64 da, db;\nsetp.eq.b32 p, %28, 0;\nmov.b64 da, {%24, %26};\nmov.b64 db, {%25, %27};\n"
        "wgmma.mma_async.sync.aligned.m64n48k16.f32.bf16.bf16 {" RL24 "}, da, db, p, 1, 1, 0, 0;\n}\n"
        : R24("+f", d, 0)
        : "r"(da), "r"(db), "n"(HI_C), "n"(HI_W), "n"(INIT));
  }
}
__device__ __forceinline__ void wg_fence() { asm volatile("wgmma.fence.sync.aligned;" ::: "memory"); }
__device__ __forceinline__ void wg_commit() { asm volatile("wgmma.commit_group.sync.aligned;" ::: "memory"); }
template <int K>
__device__ __forceinline__ void sched_cut(uint32_t x) {
  asm volatile("{\n.reg .pred p;\nsetp.eq.u32 p, %0, %1;\n@p trap;\n}\n" ::"r"(x), "n"(100000 + K) : "memory");
}
template <int N>
__device__ __forceinline__ void wg_wait() {
  asm volatile("wgmma.wait_group.sync.aligned %0;" ::"n"(N) : "memory");
}
template <int N>
__device__ __forceinline__ void fence_regs(float (&a)[N]) {
#pragma unroll
  for (int i = 0; i < N; i++) asm volatile("" : "+f"(a[i])::"memory");
}
constexpr uint32_t SB0 = 0x400;
__host__ __device__ constexpr uint32_t make_desc(uint32_t saddr, uint32_t lbo) {
  return ((saddr & 0x3FFFF) >> 4) | ((lbo >> 4) << 16);
}
__device__ __forceinline__ void fence_async_smem() { asm volatile("fence.proxy.async.shared::cta;" ::: "memory"); }
__device__ __forceinline__ void keep(const uint32_t (&f)[12]) {
#pragma unroll
  for (int i = 0; i < 12; i++) asm volatile("" ::"r"(f[i]) : "memory");
}

__device__ __forceinline__ uint32_t pack_bf16(float lo, float hi) {
  uint32_t r;
  asm("cvt.rn.bf16x2.f32 %0, %1, %2;" : "=r"(r) : "f"(hi), "f"(lo));
  return r;
}
__device__ __forceinline__ uint32_t hadd2(uint32_t a, uint32_t b) {
  uint32_t r;
  asm("add.rn.bf16x2 %0, %1, %2;" : "=r"(r) : "r"(a), "r"(b));
  return r;
}
__device__ __forceinline__ uint32_t hsub2(uint32_t a, uint32_t b) {
  uint32_t r;
  asm("sub.rn.bf16x2 %0, %1, %2;" : "=r"(r) : "r"(a), "r"(b));
  return r;
}
__device__ __forceinline__ float bf_lo(uint32_t a) { return __uint_as_float(a << 16); }
__device__ __forceinline__ float bf_hi(uint32_t a) { return __uint_as_float(a & 0xffff0000u); }

__device__ __forceinline__ uint4 ldg128(const void* p) {
  uint4 v;
  asm volatile("ld.global.nc.L1::no_allocate.v4.u32 {%0,%1,%2,%3}, [%4];"
               : "=r"(v.x), "=r"(v.y), "=r"(v.z), "=r"(v.w)
               : "l"(p));
  return v;
}
__device__ __forceinline__ uint2 ldg64(const void* p) {
  uint2 v;
  asm volatile("ld.global.nc.L1::no_allocate.v2.u32 {%0,%1}, [%2];" : "=r"(v.x), "=r"(v.y) : "l"(p));
  return v;
}
__device__ __forceinline__ void sts128(uint32_t a, uint32_t x, uint32_t y, uint32_t z, uint32_t w) {
  asm volatile("st.shared.v4.u32 [%0], {%1,%2,%3,%4};" ::"r"(a), "r"(x), "r"(y), "r"(z), "r"(w) : "memory");
}
__device__ __forceinline__ void sts24_pred(uint32_t a, const uint32_t (&v)[6], uint32_t pred) {
  asm volatile(
      "{\n.reg .pred p;\nsetp.ne.b32 p, %7, 0;\n"
      "@p st.shared.v4.u32 [%0], {%1,%2,%3,%4};\n"
      "@p st.shared.v2.u32 [%0+16], {%5,%6};\n}\n" ::"r"(a),
      "r"(v[0]), "r"(v[1]), "r"(v[2]), "r"(v[3]), "r"(v[4]), "r"(v[5]), "r"(pred)
      : "memory");
}
__device__ __forceinline__ uint4 lds128(uint32_t a) {
  uint4 v;
  asm volatile("ld.volatile.shared.v4.u32 {%0,%1,%2,%3}, [%4];" : "=r"(v.x), "=r"(v.y), "=r"(v.z), "=r"(v.w) : "r"(a) : "memory");
  return v;
}
__device__ __forceinline__ uint2 lds64(uint32_t a) {
  uint2 v;
  asm volatile("ld.volatile.shared.v2.u32 {%0,%1}, [%2];" : "=r"(v.x), "=r"(v.y) : "r"(a) : "memory");
  return v;
}
__device__ __forceinline__ void mbar_init(uint32_t bar, uint32_t cnt) {
  asm volatile("mbarrier.init.shared::cta.b64 [%0], %1;" ::"r"(bar), "r"(cnt) : "memory");
}
__device__ __forceinline__ void mbar_expect_tx(uint32_t bar, uint32_t bytes) {
  asm volatile("mbarrier.arrive.expect_tx.shared::cta.b64 _, [%0], %1;" ::"r"(bar), "r"(bytes) : "memory");
}
__device__ __forceinline__ void mbar_wait(uint32_t bar, uint32_t parity) {
  uint32_t ok;
  int it = 0;
  do {
    asm volatile(
        "{\n.reg .pred p;\n"
        "mbarrier.try_wait.parity.shared::cta.b64 p, [%1], %2;\n"
        "selp.u32 %0, 1, 0, p;\n}\n"
        : "=r"(ok)
        : "r"(bar), "r"(parity)
        : "memory");
    if (++it > (1 << 22)) __trap();
  } while (!ok);
}
__device__ __forceinline__ uint32_t mbar_try(uint32_t bar, uint32_t parity) {
  uint32_t ok;
  asm volatile(
      "{\n.reg .pred p;\n"
      "mbarrier.test_wait.parity.shared::cta.b64 p, [%1], %2;\n"
      "selp.u32 %0, 1, 0, p;\n}\n"
      : "=r"(ok)
      : "r"(bar), "r"(parity)
      : "memory");
  return ok;
}
__device__ __forceinline__ void mbar_arrive(uint32_t bar) {
  asm volatile("mbarrier.arrive.shared::cta.b64 _, [%0];" ::"r"(bar) : "memory");
}
__device__ __forceinline__ void mbar_arrive_remote(uint32_t rbar) {
  asm volatile("mbarrier.arrive.shared::cluster.b64 _, [%0];" ::"r"(rbar) : "memory");
}
__device__ __forceinline__ uint32_t mapa(uint32_t a, uint32_t rank) {
  uint32_t r;
  asm("mapa.shared::cluster.u32 %0, %1, %2;" : "=r"(r) : "r"(a), "r"(rank));
  return r;
}
__device__ __forceinline__ void st_async128(uint32_t ra, uint32_t x, uint32_t y, uint32_t z, uint32_t w, uint32_t rbar) {
  asm volatile("st.async.weak.shared::cluster.mbarrier::complete_tx::bytes.v4.b32 [%0], {%1,%2,%3,%4}, [%5];" ::"r"(ra),
               "r"(x), "r"(y), "r"(z), "r"(w), "r"(rbar)
               : "memory");
}
__device__ __forceinline__ void tma_row(uint32_t dst, const CUtensorMap* map, int grp, uint32_t bar) {
  asm volatile(
      "cp.async.bulk.tensor.5d.shared::cluster.global.mbarrier::complete_tx::bytes [%0], [%1, {%3, %3, %3, %4, %3}], "
      "[%2];" ::"r"(dst),
      "l"(map), "r"(bar), "r"(0), "r"(grp)
      : "memory");
}
__device__ __forceinline__ void tma_col(uint32_t dst, const CUtensorMap* map, int y, int x, uint32_t bar) {
  asm volatile(
      "cp.async.bulk.tensor.4d.shared::cluster.global.mbarrier::complete_tx::bytes [%0], [%1, {%3, %4, %3, %5}], "
      "[%2];" ::"r"(dst),
      "l"(map), "r"(bar), "r"(0), "r"(y), "r"(x)
      : "memory");
}
__device__ __forceinline__ void cluster_arrive() { asm volatile("barrier.cluster.arrive.release.aligned;" ::: "memory"); }
__device__ __forceinline__ void cluster_wait() { asm volatile("barrier.cluster.wait.acquire.aligned;" ::: "memory"); }

__device__ __forceinline__ uint32_t wsel(const uint4& v, int i) { return i == 0 ? v.x : i == 1 ? v.y : i == 2 ? v.z : v.w; }
__device__ __forceinline__ int cmap(int j, int q, int e) { return j < 4 ? 8 * q + 2 * j + e : 32 + 4 * q + 2 * (j - 4) + e; }

struct DRow {
  uint32_t o0[6], o1[6];
};
struct PRow {
  uint4 a;
  uint2 b;
};
__device__ __forceinline__ uint32_t pw(const PRow& p, int j) {
  return j == 0 ? p.a.x : j == 1 ? p.a.y : j == 2 ? p.a.z : j == 3 ? p.a.w : j == 4 ? p.b.x : p.b.y;
}
template <bool ADD>
__device__ __forceinline__ uint32_t top(uint32_t a, uint32_t b) {
  return ADD ? hadd2(a, b) : hsub2(a, b);
}
template <bool ADD>
__device__ __forceinline__ void edges(uint32_t (&te)[6], uint32_t ra, uint32_t rb) {
  const uint4 a = lds128(ra), b = lds128(rb);
  const uint2 c = lds64(ra + 16), d = lds64(rb + 16);
  te[0] = top<ADD>(a.x, b.x);
  te[1] = top<ADD>(a.y, b.y);
  te[2] = top<ADD>(a.z, b.z);
  te[3] = top<ADD>(a.w, b.w);
  te[4] = top<ADD>(c.x, d.x);
  te[5] = top<ADD>(c.y, d.y);
}
template <bool ADD>
__device__ __forceinline__ void frags(uint32_t (&f)[12], const DRow& a, const DRow& b, const uint32_t (&te)[6], int ks,
                                      bool e0, bool e7) {
#pragma unroll
  for (int i = 0; i < 2; i++) {
    const int j = 2 * ks + i;
    const uint32_t t0 = top<ADD>(a.o0[j], b.o0[j]), t1 = top<ADD>(a.o1[j], b.o1[j]);
    const uint32_t nA = __shfl_up_sync(0xffffffffu, t1, 4);
    const uint32_t nB = __shfl_down_sync(0xffffffffu, t0, 4);
    f[0 + 2 * i] = e0 ? te[j] : nA;
    f[1 + 2 * i] = t0;
    f[4 + 2 * i] = t0;
    f[5 + 2 * i] = t1;
    f[8 + 2 * i] = t1;
    f[9 + 2 * i] = e7 ? te[j] : nB;
  }
}
template <int MODE>
__device__ __forceinline__ void fr1(uint32_t (&f)[12], const DRow& a, const DRow& b, int ks) {
#pragma unroll
  for (int i = 0; i < 2; i++) {
    const int j = 2 * ks + i;
    const uint32_t t0 = MODE == 0 ? a.o0[j] : top<MODE == 1>(a.o0[j], b.o0[j]);
    const uint32_t t1 = MODE == 0 ? a.o1[j] : top<MODE == 1>(a.o1[j], b.o1[j]);
    f[0 + 2 * i] = __shfl_up_sync(0xffffffffu, t1, 4);
    f[9 + 2 * i] = __shfl_down_sync(0xffffffffu, t0, 4);
    f[1 + 2 * i] = t0;
    f[4 + 2 * i] = t0;
    f[5 + 2 * i] = t1;
    f[8 + 2 * i] = t1;
  }
}
__device__ __forceinline__ void fr2(uint32_t (&f)[12], const uint32_t (&te)[6], int ks, bool e0, bool e7) {
#pragma unroll
  for (int i = 0; i < 2; i++) {
    f[0 + 2 * i] = e0 ? te[2 * ks + i] : f[0 + 2 * i];
    f[9 + 2 * i] = e7 ? te[2 * ks + i] : f[9 + 2 * i];
    asm volatile("" : "+r"(f[0 + 2 * i]), "+r"(f[9 + 2 * i]));
  }
}
struct ERaw {
  uint4 a, b;
  uint2 c, d;
};
__device__ __forceinline__ void ed1(ERaw& r, uint32_t ra, uint32_t rb) {
  r.a = lds128(ra);
  r.b = lds128(rb);
  r.c = lds64(ra + 16);
  r.d = lds64(rb + 16);
}
template <bool ADD>
__device__ __forceinline__ void ed2(uint32_t (&te)[6], const ERaw& r) {
  te[0] = top<ADD>(r.a.x, r.b.x);
  te[1] = top<ADD>(r.a.y, r.b.y);
  te[2] = top<ADD>(r.a.z, r.b.z);
  te[3] = top<ADD>(r.a.w, r.b.w);
  te[4] = top<ADD>(r.c.x, r.d.x);
  te[5] = top<ADD>(r.c.y, r.d.y);
}
template <int INIT>
__device__ __forceinline__ void conv_group(float (&acc)[48], const uint32_t (&f)[12], uint32_t dB, int pos, int ks) {
  wg_fence();
  wgmma_rs_n96<INIT>(acc, f[0], f[1], f[2], f[3], dB + (uint32_t)(((3 * pos + 0) * UT + 2 * ks * 1536) >> 4));
  wgmma_rs_n96<0>(acc, f[4], f[5], f[6], f[7], dB + (uint32_t)(((3 * pos + 1) * UT + 2 * ks * 1536) >> 4));
  wgmma_rs_n96<0>(acc, f[8], f[9], f[10], f[11], dB + (uint32_t)(((3 * pos + 2) * UT + 2 * ks * 1536) >> 4));
  wg_commit();
}
template <int CH, int INIT>
__device__ __forceinline__ void lateral(float (&acc)[24], uint32_t dA, uint32_t dwl) {
  wg_fence();
#pragma unroll
  for (int k = 0; k < 6; k++) {
    const uint32_t a = dA + (uint32_t)(((k >> 1) * CH + (k & 1) * 32) >> 4);
    const uint32_t b = dwl + (uint32_t)(k * 1536 >> 4);
    if (k == 0)
      wgmma_ss_n48<INIT>(acc, a, b);
    else
      wgmma_ss_n48<0>(acc, a, b);
  }
  wg_commit();
}

#define AI __attribute__((always_inline))
template <int V>
struct IC {
  static constexpr int value = V;
};

template <int RANK>
__device__ __forceinline__ void fpn_body(const CUtensorMap& map_row, const CUtensorMap& map_col,
                                         const __nv_bfloat16* __restrict__ p_coarse,
                                         const __nv_bfloat16* __restrict__ w_lat,
                                         const __nv_bfloat16* __restrict__ w_out, __nv_bfloat16* __restrict__ out) {
  extern __shared__ __align__(1024) unsigned char smem[];
  const uint32_t sb = (uint32_t)__cvta_generic_to_shared(smem);
  if ((sb & 0xFFFFFFu) != SB0) __trap();
  const int tid = threadIdx.x;
  const int wg = __shfl_sync(0xffffffffu, tid >> 7, 0);
  const int t128 = tid & 127;
  const int w = __shfl_sync(0xffffffffu, (tid >> 5) & 3, 0);
  const int lane = tid & 31;
  const int g = lane >> 2, q = lane & 3;
  constexpr uint32_t rank = RANK;
  const int cl = blockIdx.x >> 1;
  const int y0 = (cl >> 2) * 32;
  const int x0 = ((cl & 3) * 2 + wg) * 64;

  if (tid == 0) {
#pragma unroll
    for (int i = 0; i < 2; i++) {
      const uint32_t b = sb + OFF_BAR + i * 64;
      mbar_init(b + 0, 1);
      mbar_init(b + 8, 1);
      mbar_init(b + 16, 1);
      mbar_init(b + 24, 1);
      mbar_init(b + 32, 4);
      mbar_init(b + 40, 4);
      mbar_init(b + 48, 1);
      mbar_init(b + 56, 4);
    }
    asm volatile("fence.mbarrier_init.release.cluster;" ::: "memory");
    fence_async_smem();
#pragma unroll
    for (int i = 0; i < 2; i++) {
      const uint32_t b = sb + OFF_BAR + i * 64;
      const int xw = ((cl & 3) * 2 + i) * 64;
      mbar_expect_tx(b + 48, 2 * HTILE);
      tma_col(sb + OFF_X + i * X_BYTES, &map_col, y0 - 1, xw - 1, b + 48);
      tma_col(sb + OFF_X + i * X_BYTES + HTILE, &map_col, y0 - 1, xw + 64, b + 48);
      mbar_expect_tx(b + 0, CSLOT);
      tma_row(sb + OFF_C + i * 2 * CSLOT, &map_row, (y0 - 1) * 32 + (xw >> 4), b + 0);
      mbar_expect_tx(b + 8, CSLOT);
      tma_row(sb + OFF_C + i * 2 * CSLOT + CSLOT, &map_row, y0 * 32 + (xw >> 4), b + 8);
      mbar_expect_tx(b + 16, XROW);
      mbar_expect_tx(b + 24, XROW);
    }
  }
  cluster_arrive();

  const unsigned char* pc = (const unsigned char*)p_coarse + 96 * rank;

  PRow hp[2][2], pA, pp;
  bool hv[2][2];
#pragma unroll
  for (int sd = 0; sd < 2; sd++)
#pragma unroll
    for (int h = 0; h < 2; h++) {
      const int hr = 16 * w + 8 * h + g, yy = y0 - 1 + hr, xx = sd ? x0 + 64 : x0 - 1;
      hv[sd][h] = hr < 34 && yy >= 0 && yy < IMG && xx >= 0 && xx < IMG;
      const unsigned char* a = pc + (hv[sd][h] ? ((size_t)(yy >> 1) * 256 + (xx >> 1)) * 192 : 0);
      hp[sd][h].a = ldg128(a + 16 * q);
      hp[sd][h].b = ldg64(a + 64 + 8 * q);
    }
  uint32_t poff = ((y0 >> 1) * 256 + (x0 >> 1) + 8 * w + g) * 192 + 16 * q;
  {
    const unsigned char* a = pc + poff - (y0 > 0 ? 49152 : 0);
    pA.a = ldg128(a);
    pA.b = ldg64(a + 64 - 8 * q);
    pp.a = ldg128(pc + poff);
    pp.b = ldg64(pc + poff + 64 - 8 * q);
    poff += 49152;
  }

  if (tid < 216) {
    const int dj = tid / 72, rem = tid % 72, kc = rem / 12, u = rem % 12;
    const unsigned char* src = (const unsigned char*)w_out + ((size_t)(dj * 96 + 48 * rank) * 96 + 8 * u) * 2;
    uint4 v[3][8];
#pragma unroll
    for (int kk = 0; kk < 8; kk++) {
      const int ci = cmap(kc, kk >> 1, kk & 1);
#pragma unroll
      for (int di = 0; di < 3; di++) v[di][kk] = ldg128(src + (size_t)di * 3 * 96 * 192 + ci * 192);
    }
    const uint32_t base = sb + OFF_U + dj * UT + kc * 1536 + (8 * (4 * (u >> 2)) + 2 * (u & 3)) * 16;
#pragma unroll
    for (int wd = 0; wd < 4; wd++) {
      uint32_t u0[2][4], u1[2][4], u2[2][4], u3[2][4];
#pragma unroll
      for (int kp = 0; kp < 4; kp++) {
        const uint32_t a0 = wsel(v[0][2 * kp], wd), a1 = wsel(v[0][2 * kp + 1], wd);
        const uint32_t b0 = wsel(v[1][2 * kp], wd), b1 = wsel(v[1][2 * kp + 1], wd);
        const uint32_t c0 = wsel(v[2][2 * kp], wd), c1 = wsel(v[2][2 * kp + 1], wd);
        u0[0][kp] = __byte_perm(a0, a1, 0x5410);
        u0[1][kp] = __byte_perm(a0, a1, 0x7632);
        u3[0][kp] = __byte_perm(c0, c1, 0x5410);
        u3[1][kp] = __byte_perm(c0, c1, 0x7632);
        const float s0l = bf_lo(a0) + bf_lo(c0), s1l = bf_lo(a1) + bf_lo(c1);
        const float s0h = bf_hi(a0) + bf_hi(c0), s1h = bf_hi(a1) + bf_hi(c1);
        u1[0][kp] = pack_bf16((s0l + bf_lo(b0)) * 0.5f, (s1l + bf_lo(b1)) * 0.5f);
        u1[1][kp] = pack_bf16((s0h + bf_hi(b0)) * 0.5f, (s1h + bf_hi(b1)) * 0.5f);
        u2[0][kp] = pack_bf16((s0l - bf_lo(b0)) * 0.5f, (s1l - bf_lo(b1)) * 0.5f);
        u2[1][kp] = pack_bf16((s0h - bf_hi(b0)) * 0.5f, (s1h - bf_hi(b1)) * 0.5f);
      }
#pragma unroll
      for (int e = 0; e < 2; e++) {
        const uint32_t a = base + (8 * wd + e) * 16;
        sts128(a, u0[e][0], u0[e][1], u0[e][2], u0[e][3]);
        sts128(a + 3 * UT, u1[e][0], u1[e][1], u1[e][2], u1[e][3]);
        sts128(a + 6 * UT, u2[e][0], u2[e][1], u2[e][2], u2[e][3]);
        sts128(a + 9 * UT, u3[e][0], u3[e][1], u3[e][2], u3[e][3]);
      }
    }
  } else {
    for (int blk = tid - 216; blk < 72; blk += 40) {
      const int kc = blk / 6, u = blk % 6;
      uint4 v[8];
#pragma unroll
      for (int kk = 0; kk < 8; kk++)
        v[kk] = ldg128((const unsigned char*)w_lat + ((size_t)(8 * kc + kk) * 96 + 48 * rank + 8 * u) * 2);
#pragma unroll
      for (int wd = 0; wd < 4; wd++) {
        const int n = u < 4 ? 8 * wd + 2 * u : 8 * (4 + (wd & 1)) + 2 * (2 * (u - 4) + (wd >> 1));
        const uint32_t a = sb + OFF_WL + kc * 768 + n * 16;
        uint32_t lo[4], hi[4];
#pragma unroll
        for (int kp = 0; kp < 4; kp++) {
          lo[kp] = __byte_perm(wsel(v[2 * kp], wd), wsel(v[2 * kp + 1], wd), 0x5410);
          hi[kp] = __byte_perm(wsel(v[2 * kp], wd), wsel(v[2 * kp + 1], wd), 0x7632);
        }
        sts128(a, lo[0], lo[1], lo[2], lo[3]);
        sts128(a + 16, hi[0], hi[1], hi[2], hi[3]);
      }
    }
  }
  fence_async_smem();
  __syncthreads();
  cluster_wait();

  const uint32_t bb = sb + OFF_BAR + wg * 64;
  constexpr uint32_t dwl = make_desc(SB0 + OFF_WL, 768);
  constexpr uint32_t dB = make_desc(SB0 + OFF_U, 1536);
  const uint32_t cs = sb + OFF_C + wg * 2 * CSLOT;
  const uint32_t dC = make_desc(SB0 + OFF_C, 16) + wg * (2 * CSLOT >> 4);
  const uint32_t xbase = sb + OFF_X + wg * X_BYTES;
  const uint32_t dH = make_desc(SB0 + OFF_X, 16) + wg * (X_BYTES >> 4);
  const uint32_t hb = sb + OFF_H + wg * H_BYTES;
  const uint32_t eb = sb + OFF_E + wg * E_BYTES;
  const uint32_t xa = xbase + t128 * 16;
  const uint32_t peer = rank ^ 1;
  const uint32_t rdelta = __shfl_sync(0xffffffffu, mapa(bb, peer) - bb, 0);
#define r_xa (xa + rdelta)
#define r_bb (bb + rdelta)
  const int grp0 = (y0 - 1) * 32 + (x0 >> 4);
  const bool last_block = (y0 + 32 == IMG);

  const bool e0 = g == 0, e7 = g == 7;
  const bool halo_lane = (w == 0 && g < 4) || (w == 3 && g >= 4);
  const uint32_t ewr = eb + (2 * w + (e7 ? 1 : 0)) * 512 + 32 * q;
  const uint32_t erd =
      (halo_lane ? (g < 4 ? hb : hb + HSIDE) : (g < 4 ? eb + (2 * w - 1) * 512 : eb + (2 * w + 2) * 512)) + 32 * q;
  const uint32_t emask = halo_lane ? 0xFFFFu : 511u;
  auto er = [&](int k) AI { return erd + (((uint32_t)k << 8) & emask); };

  float ax[48], ay[48], lat[24];
  DRow d1, d2, t0, t3;
  uint32_t f0[12], f1[12], f2[12], te[6], kp[12];
#pragma unroll
  for (int i = 0; i < 12; i++) kp[i] = 0;

  auto d_pack = [&](auto MODE, int i, DRow& d, DRow& t, const float(&acc)[24], const PRow& p, bool zero) AI {
    constexpr int mode = decltype(MODE)::value;
#pragma unroll
    for (int j = 0; j < 6; j++) {
      uint32_t n0 = hadd2(pack_bf16(acc[4 * j], acc[4 * j + 1]), pw(p, j));
      uint32_t n1 = hadd2(pack_bf16(acc[4 * j + 2], acc[4 * j + 3]), pw(p, j));
      if (zero) n0 = n1 = 0;
      if (mode == 1) {
        t.o0[j] = hsub2(n0, d.o0[j]);
        t.o1[j] = hsub2(n1, d.o1[j]);
      }
      if (mode == 2) {
        t.o0[j] = hsub2(d.o0[j], n0);
        t.o1[j] = hsub2(d.o1[j], n1);
      }
      d.o0[j] = n0;
      d.o1[j] = n1;
    }
    uint32_t ev[6];
#pragma unroll
    for (int j = 0; j < 6; j++) ev[j] = e0 ? d.o0[j] : d.o1[j];
    sts24_pred(ewr + (i & 3) * 128, ev, e0 || e7);
    __syncwarp();
    if (lane == 0) mbar_arrive(bb + 56);
  };
  auto refill = [&](int i) AI {
    if (t128 == 0 && i + 2 <= 33) {
      mbar_expect_tx(bb + (i & 1) * 8, CSLOT);
      tma_row(cs + (i & 1) * CSLOT, &map_row, grp0 + (i + 2) * 32, bb + (i & 1) * 8);
    }
  };
  auto send = [&](const float(&acc)[48], int b) AI {
    constexpr int rk = RANK;
#pragma unroll
    for (int J = 0; J < 3; J++) {
      uint32_t sd[4];
#pragma unroll
      for (int i = 0; i < 4; i++) {
        const int j = 4 * J + i;
        sd[i] = pack_bf16(acc[4 * j + 2 - 2 * rk], acc[4 * j + 3 - 2 * rk]);
        kp[j] = pack_bf16(acc[4 * j + 2 * rk], acc[4 * j + 2 * rk + 1]);
      }
      st_async128(r_xa + b * XROW + J * 2048, sd[0], sd[1], sd[2], sd[3], r_bb + 16 + 8 * b);
    }
  };
  uint32_t ooff = ((y0 * IMG) + x0 + 16 * w + 2 * g + rank) * 192 + 16 * q;
  uint4 xr[3];
  auto fin1 = [&](int b) AI {
#pragma unroll
    for (int J = 0; J < 3; J++) xr[J] = lds128(xa + b * XROW + J * 2048);
  };
  auto fin2 = [&](int b, uint32_t parity, uint32_t ok, bool more) AI {
    if (!ok) {
      mbar_wait(bb + 16 + 8 * b, parity);
      fin1(b);
    }
    if (more && t128 == 0) mbar_expect_tx(bb + 16 + 8 * b, XROW);
#pragma unroll
    for (int J = 0; J < 3; J++) {
      uint4 o;
      o.x = hadd2(kp[4 * J + 0], xr[J].x);
      o.y = hadd2(kp[4 * J + 1], xr[J].y);
      o.z = hadd2(kp[4 * J + 2], xr[J].z);
      o.w = hadd2(kp[4 * J + 3], xr[J].w);
      *(uint4*)((unsigned char*)out + (ooff + 64 * J)) = o;
    }
    ooff += 98304;
    __syncwarp();
    if (more && lane == 0) mbar_arrive_remote(r_bb + 32 + 8 * b);
  };

  {
    float lat2[24];
    mbar_wait(bb + 48, 0);
    lateral<2560, 1>(lat, dH, dwl);
    lateral<2560, 1>(lat2, dH + (HTILE >> 4), dwl);
    wg_wait<0>();
    fence_regs(lat);
    fence_regs(lat2);
    __syncwarp();
    if (lane == 0) {
      mbar_arrive_remote(r_bb + 32);
      mbar_arrive_remote(r_bb + 40);
    }
#pragma unroll
    for (int h = 0; h < 2; h++) {
      const int hr = 16 * w + 8 * h + g;
      uint32_t v0[6], v1[6];
#pragma unroll
      for (int j = 0; j < 6; j++) {
        v0[j] = hv[0][h] ? hadd2(pack_bf16(lat[4 * j + 2 * h], lat[4 * j + 2 * h + 1]), pw(hp[0][h], j)) : 0u;
        v1[j] = hv[1][h] ? hadd2(pack_bf16(lat2[4 * j + 2 * h], lat2[4 * j + 2 * h + 1]), pw(hp[1][h], j)) : 0u;
      }
      sts24_pred(hb + hr * 128 + 32 * q, v0, hr < 34);
      sts24_pred(hb + HSIDE + hr * 128 + 32 * q, v1, hr < 34);
    }
    mbar_wait(bb + 0, 0);
    lateral<4096, 1>(lat, dC, dwl);
    mbar_wait(bb + 8, 0);
    lateral<4096, 1>(lat2, dC + (CSLOT >> 4), dwl);
    wg_wait<0>();
    fence_regs(lat);
    fence_regs(lat2);
    d_pack(IC<0>{}, 0, d2, t0, lat, pA, y0 == 0);
    mbar_wait(bb + 56, 0);
    refill(0);
    d_pack(IC<0>{}, 1, d1, t3, lat2, pp, false);
    mbar_wait(bb + 56, 1);
    refill(1);
    mbar_wait(bb + 0, 1);
    lateral<4096, 1>(lat, dC, dwl);
    wg_wait<0>();
    fence_regs(lat);
    d_pack(IC<2>{}, 2, d2, t0, lat, pp, false);
    mbar_wait(bb + 56, 0);
    refill(2);
    pp.a = ldg128(pc + poff);
    pp.b = ldg64(pc + poff + 64 - 8 * q);
    edges<true>(te, er(0) + 128, er(1));
    frags<true>(f0, d1, d2, te, 0, e0, e7);
    conv_group<1>(ax, f0, dB, 1, 0);
    frags<true>(f1, d1, d2, te, 1, e0, e7);
  }

  ERaw er4;
  uint32_t ok1, ok2;
#define CUT sched_cut<__LINE__>(cl)
  auto stepA = [&](auto FIRST, int s) AI {
    constexpr bool notfirst = !decltype(FIRST)::value;
    const uint32_t par = s & 1;
    wg_wait<1>();
    if (notfirst) fence_regs(ay);
    CUT;
    fr1<1>(f2, d1, d2, 2);
    if (notfirst) {
      ok1 = mbar_try(bb + 16, par ^ 1);
      fin1(0);
    }
    CUT;
    conv_group<0>(ax, f1, dB, 1, 1);
    CUT;
    if (notfirst) fin2(0, par ^ 1, ok1, true);
    fr2(f2, te, 2, e0, e7);
    wg_wait<1>();
    CUT;
    ed1(er4, er(s + 1), er(s) + 128);
    fr1<2>(f0, d2, d1, 0);
    if (notfirst) ok2 = mbar_try(bb + 40, par ^ 1);
    CUT;
    conv_group<0>(ax, f2, dB, 1, 2);
    CUT;
    if (notfirst) {
      if (!ok2) mbar_wait(bb + 40, par ^ 1);
      send(ay, 1);
    }
    ed2<false>(te, er4);
    fr2(f0, te, 0, e0, e7);
    wg_wait<1>();
    CUT;
    fr1<2>(f1, d2, d1, 1);
    CUT;
    conv_group<notfirst ? 2 : 1>(ay, f0, dB, 2, 0);
    CUT;
    fr2(f1, te, 1, e0, e7);
    wg_wait<1>();
    CUT;
    fr1<2>(f2, d2, d1, 2);
    CUT;
    conv_group<0>(ay, f1, dB, 2, 1);
    CUT;
    fr2(f2, te, 2, e0, e7);
    wg_wait<1>();
    CUT;
    ed1(er4, er(s), er(s + 1));
    fr1<0>(f0, t0, t0, 0);
    ok1 = mbar_try(bb + 8, par ^ 1);
    CUT;
    conv_group<0>(ay, f2, dB, 2, 2);
    CUT;
    ed2<false>(te, er4);
    fr2(f0, te, 0, e0, e7);
    if (!ok1) mbar_wait(bb + 8, par ^ 1);
    wg_wait<1>();
    CUT;
    fr1<0>(f1, t0, t0, 1);
    CUT;
    lateral<4096, 2>(lat, dC + (CSLOT >> 4), dwl);
    CUT;
    fr2(f1, te, 1, e0, e7);
    CUT;
    wg_wait<1>();
    fence_regs(ax);
    fence_regs(ay);
  };
  auto stepB = [&](auto LAST, int s) AI {
    constexpr bool notlast = !decltype(LAST)::value;
    const uint32_t par = s & 1;
    fr1<0>(f2, t0, t0, 2);
    if (notlast) ok2 = mbar_try(bb + 0, par);
    CUT;
#pragma unroll
    for (int i = 0; i < 48; i++) {
      asm volatile("add.f32 %0, %0, %1;\n\tfma.rn.f32 %1, %1, 0fC0000000, %0;" : "+f"(ax[i]), "+f"(ay[i]));
    }
    fence_regs(ax);
    fence_regs(ay);
    conv_group<0>(ax, f0, dB, 0, 0);
    wg_wait<1>();
    fence_regs(lat);
    CUT;
    d_pack(IC<1>{}, 2 * s + 3, d1, t3, lat, pp, last_block && !notlast);
    fr2(f2, te, 2, e0, e7);
    if (notlast && !ok2) mbar_wait(bb + 0, par);
    ok1 = mbar_try(bb + 24, par ^ 1);
    fin1(1);
    CUT;
    if (notlast) lateral<4096, 2>(lat, dC, dwl);
    CUT;
    if (s > 0) fin2(1, par ^ 1, ok1, true);
    wg_wait<notlast ? 1 : 0>();
    CUT;
    ok1 = mbar_try(bb + 56, 1);
    ed1(er4, er(s + 1) + 128, er(s) + 128);
    fr1<0>(f0, t3, t3, 0);
    CUT;
    conv_group<0>(ax, f1, dB, 0, 1);
    CUT;
    if (!ok1) {
      mbar_wait(bb + 56, 1);
      ed1(er4, er(s + 1) + 128, er(s) + 128);
    }
    refill(2 * s + 3);
    ed2<false>(te, er4);
    fr2(f0, te, 0, e0, e7);
    if (notlast) {
      wg_wait<1>();
      fence_regs(lat);
      CUT;
      d_pack(IC<2>{}, 2 * s + 4, d2, t0, lat, pp, false);
      if ((y0 >> 1) + s + 2 < 256) poff += 49152;
      pp.a = ldg128(pc + poff);
      pp.b = ldg64(pc + poff + 64 - 8 * q);
    }
    CUT;
    conv_group<0>(ax, f2, dB, 0, 2);
    wg_wait<1>();
    keep(f1);
    CUT;
    fr1<0>(f1, t3, t3, 1);
    if (notlast) ok1 = mbar_try(bb + 56, 0);
    CUT;
    conv_group<0>(ay, f0, dB, 3, 0);
    CUT;
    fr2(f1, te, 1, e0, e7);
    if (notlast) {
      if (!ok1) mbar_wait(bb + 56, 0);
      refill(2 * s + 4);
    }
    wg_wait<1>();
    fence_regs(ax);
    keep(f2);
    CUT;
    fr1<0>(f2, t3, t3, 2);
    ok2 = mbar_try(bb + 32, par);
    CUT;
    conv_group<0>(ay, f1, dB, 3, 1);
    CUT;
    if (!ok2) mbar_wait(bb + 32, par);
    send(ax, 0);
    fr2(f2, te, 2, e0, e7);
    if (notlast) {
      wg_wait<1>();
      CUT;
      ed1(er4, er(s + 1) + 128, er(s + 2));
      fr1<1>(f0, d1, d2, 0);
    }
    CUT;
    conv_group<0>(ay, f2, dB, 3, 2);
    if (notlast) {
      CUT;
      ed2<true>(te, er4);
      fr2(f0, te, 0, e0, e7);
      wg_wait<1>();
      CUT;
      fr1<1>(f1, d1, d2, 1);
      CUT;
      conv_group<2>(ax, f0, dB, 1, 0);
      CUT;
      fr2(f1, te, 1, e0, e7);
    }
  };

  stepA(IC<1>{}, 0);
#pragma unroll 1
  for (int s = 0; s < NSTEP - 1; s++) {
    stepB(IC<0>{}, s);
    stepA(IC<0>{}, s + 1);
  }
  stepB(IC<1>{}, NSTEP - 1);
  fin2(0, 1, 0, false);
  wg_wait<0>();
  fence_regs(ay);
  mbar_wait(bb + 40, 1);
  send(ay, 1);
  fin2(1, 1, 0, false);
  cluster_arrive();
  cluster_wait();
}

__global__ void __cluster_dims__(2, 1, 1) __launch_bounds__(256, 1)
    fpn_kernel(const __grid_constant__ CUtensorMap map_row, const __grid_constant__ CUtensorMap map_col,
               const __nv_bfloat16* __restrict__ p_coarse, const __nv_bfloat16* __restrict__ w_lat,
               const __nv_bfloat16* __restrict__ w_out, __nv_bfloat16* __restrict__ out) {
  uint32_t rank;
  asm("mov.u32 %0, %%cluster_ctarank;" : "=r"(rank));
  if (rank)
    fpn_body<1>(map_row, map_col, p_coarse, w_lat, w_out, out);
  else
    fpn_body<0>(map_row, map_col, p_coarse, w_lat, w_out, out);
}

typedef CUresult (*EncodeFn)(CUtensorMap*, CUtensorMapDataType, cuuint32_t, void*, const cuuint64_t*, const cuuint64_t*,
                             const cuuint32_t*, const cuuint32_t*, CUtensorMapInterleave, CUtensorMapSwizzle,
                             CUtensorMapL2promotion, CUtensorMapFloatOOBfill);

}

extern "C" void kernel_launch(void* const* d_in, const int* in_sizes, int n_in, void* d_out, int out_size) {
  (void)in_sizes;
  (void)n_in;
  (void)out_size;
  static EncodeFn encode = nullptr;
  if (!encode) {
    cudaFuncSetAttribute(fpn_kernel, cudaFuncAttributeMaxDynamicSharedMemorySize, SMEM_BYTES);
    void* fn = nullptr;
    cudaDriverEntryPointQueryResult st;
    cudaGetDriverEntryPoint("cuTensorMapEncodeTiled", &fn, cudaEnableDefault, &st);
    encode = (EncodeFn)fn;
  }
  CUtensorMap map_row, map_col;
  {
    const cuuint64_t dim[5] = {32, 8, 2, 16384, 3};
    const cuuint64_t str[4] = {384, 192, 3072, 64};
    const cuuint32_t box[5] = {32, 8, 2, 4, 3};
    const cuuint32_t es[5] = {1, 1, 1, 1, 1};
    encode(&map_row, CU_TENSOR_MAP_DATA_TYPE_BFLOAT16, 5, d_in[0], dim, str, box, es, CU_TENSOR_MAP_INTERLEAVE_NONE,
           CU_TENSOR_MAP_SWIZZLE_64B, CU_TENSOR_MAP_L2_PROMOTION_L2_256B, CU_TENSOR_MAP_FLOAT_OOB_FILL_NONE);
  }
  {
    const cuuint64_t dim[4] = {32, 512, 3, 512};
    const cuuint64_t str[3] = {98304, 64, 192};
    const cuuint32_t box[4] = {32, 40, 3, 1};
    const cuuint32_t es[4] = {1, 1, 1, 1};
    encode(&map_col, CU_TENSOR_MAP_DATA_TYPE_BFLOAT16, 4, d_in[0], dim, str, box, es, CU_TENSOR_MAP_INTERLEAVE_NONE,
           CU_TENSOR_MAP_SWIZZLE_64B, CU_TENSOR_MAP_L2_PROMOTION_L2_128B, CU_TENSOR_MAP_FLOAT_OOB_FILL_NONE);
  }
  fpn_kernel<<<128, 256, SMEM_BYTES, cudaStreamPerThread>>>(map_row, map_col, (const __nv_bfloat16*)d_in[1],
                                                            (const __nv_bfloat16*)d_in[2], (const __nv_bfloat16*)d_in[3],
                                                            (__nv_bfloat16*)d_out);
}
```

```cpp
#include <cuda_runtime.h>
#include <cuda.h>
#include <cuda_bf16.h>
#include <stdint.h>

namespace {

constexpr int IMG = 512;
constexpr int CSLOT = 12288;
constexpr int UT = 9216;
constexpr int OFF_C = 0;
constexpr int OFF_U = 4 * CSLOT;
constexpr int OFF_WL = OFF_U + 12 * UT;
constexpr int OFF_X = OFF_WL + 9216;
constexpr int XROW = 6144;
constexpr int HTILE = 7680;
constexpr int X_BYTES = 2 * HTILE;
constexpr int OFF_H = OFF_X + 2 * X_BYTES;
constexpr int HSIDE = 35 * 128;
constexpr int H_BYTES = 2 * HSIDE;
constexpr int HE_BYTES = 13312;
constexpr int OFF_BAR = OFF_H + 2 * HE_BYTES;
constexpr int SMEM_BYTES = OFF_BAR + 192;
__device__ __align__(1024) unsigned char g_u[2 * 12 * UT];
__device__ unsigned int g_cnt;
constexpr int NSTEP = 16;

#define R4(c, a, o) c(a[o]), c(a[o + 1]), c(a[o + 2]), c(a[o + 3])
#define R8(c, a, o) R4(c, a, o), R4(c, a, o + 4)
#define R24(c, a, o) R8(c, a, o), R8(c, a, o + 8), R8(c, a, o + 16)
#define RL24 \
  "%0, %1, %2, %3, %4, %5, %6, %7, %8, %9, %10, %11, %12, %13, %14, %15, %16, %17, %18, %19, %20, %21, %22, %23"
#define RL48                                                                                                       \
  RL24 ", %24, %25, %26, %27, %28, %29, %30, %31, %32, %33, %34, %35, %36, %37, %38, %39, %40, %41, %42, %43, %44, " \
       "%45, %46, %47"

constexpr uint32_t HI_W = 128 >> 4;
constexpr uint32_t HI_C = (512 >> 4) | (2u << 30);
template <int INIT>
__device__ __forceinline__ void wgmma_rs_n96(float (&d)[48], uint32_t a0, uint32_t a1, uint32_t a2, uint32_t a3,
                                             uint32_t db) {
  if constexpr (INIT == 1) {
    asm volatile(
        "{\n.reg .pred p;\n.reg .b64 db;\nsetp.ne.b32 p, 0, 0;\nmov.b64 db, {%52, %53};\n"
        "wgmma.mma_async.sync.aligned.m64n96k16.f32.bf16.bf16 {" RL48 "}, {%48, %49, %50, %51}, db, p, 1, 1, 0;\n}\n"
        : R24("=f", d, 0), R24("=f", d, 24)
        : "r"(a0), "r"(a1), "r"(a2), "r"(a3), "r"(db), "n"(HI_W));
  } else {
    asm volatile(
        "{\n.reg .pred p;\n.reg .b64 db;\nsetp.eq.b32 p, %54, 0;\nmov.b64 db, {%52, %53};\n"
        "wgmma.mma_async.sync.aligned.m64n96k16.f32.bf16.bf16 {" RL48 "}, {%48, %49, %50, %51}, db, p, 1, 1, 0;\n}\n"
        : R24("+f", d, 0), R24("+f", d, 24)
        : "r"(a0), "r"(a1), "r"(a2), "r"(a3), "r"(db), "n"(HI_W), "n"(INIT));
  }
}
template <int INIT>
__device__ __forceinline__ void wgmma_ss_n48(float (&d)[24], uint32_t da, uint32_t db) {
  if constexpr (INIT == 1) {
    asm volatile(
        "{\n.reg .pred p;\n.reg .b64 da, db;\nsetp.ne.b32 p, 0, 0;\nmov.b64 da, {%24, %26};\nmov.b64 db, {%25, %27};\n"
        "wgmma.mma_async.sync.aligned.m64n48k16.f32.bf16.bf16 {" RL24 "}, da, db, p, 1, 1, 0, 0;\n}\n"
        : R24("=f", d, 0)
        : "r"(da), "r"(db), "n"(HI_C), "n"(HI_W));
  } else {
    asm volatile(
        "{\n.reg .pred p;\n.reg .b64 da, db;\nsetp.eq.b32 p, %28, 0;\nmov.b64 da, {%24, %26};\nmov.b64 db, {%25, %27};\n"
        "wgmma.mma_async.sync.aligned.m64n48k16.f32.bf16.bf16 {" RL24 "}, da, db, p, 1, 1, 0, 0;\n}\n"
        : R24("+f", d, 0)
        : "r"(da), "r"(db), "n"(HI_C), "n"(HI_W), "n"(INIT));
  }
}
__device__ __forceinline__ void wg_fence() { asm volatile("wgmma.fence.sync.aligned;" ::: "memory"); }
__device__ __forceinline__ void wg_commit() { asm volatile("wgmma.commit_group.sync.aligned;" ::: "memory"); }
template <int K>
__device__ __forceinline__ void sched_cut(uint32_t x) {
  asm volatile("{\n.reg .pred p;\nsetp.eq.u32 p, %0, %1;\n@p trap;\n}\n" ::"r"(x), "n"(100000 + K) : "memory");
}
template <int N>
__device__ __forceinline__ void wg_wait() {
  asm volatile("wgmma.wait_group.sync.aligned %0;" ::"n"(N) : "memory");
}
template <int N>
__device__ __forceinline__ void fence_regs(float (&a)[N]) {
#pragma unroll
  for (int i = 0; i < N; i++) asm volatile("" : "+f"(a[i])::"memory");
}
constexpr uint32_t SB0 = 0x400;
__host__ __device__ constexpr uint32_t make_desc(uint32_t saddr, uint32_t lbo) {
  return ((saddr & 0x3FFFF) >> 4) | ((lbo >> 4) << 16);
}
__device__ __forceinline__ void fence_async_smem() { asm volatile("fence.proxy.async.shared::cta;" ::: "memory"); }
__device__ __forceinline__ void keep(const uint32_t (&f)[12]) {
#pragma unroll
  for (int i = 0; i < 12; i++) asm volatile("" ::"r"(f[i]) : "memory");
}

__device__ __forceinline__ uint32_t pack_bf16(float lo, float hi) {
  uint32_t r;
  asm("cvt.rn.bf16x2.f32 %0, %1, %2;" : "=r"(r) : "f"(hi), "f"(lo));
  return r;
}
__device__ __forceinline__ uint32_t hadd2(uint32_t a, uint32_t b) {
  uint32_t r;
  asm("add.rn.bf16x2 %0, %1, %2;" : "=r"(r) : "r"(a), "r"(b));
  return r;
}
__device__ __forceinline__ uint32_t hsub2(uint32_t a, uint32_t b) {
  uint32_t r;
  asm("sub.rn.bf16x2 %0, %1, %2;" : "=r"(r) : "r"(a), "r"(b));
  return r;
}
__device__ __forceinline__ float bf_lo(uint32_t a) { return __uint_as_float(a << 16); }
__device__ __forceinline__ float bf_hi(uint32_t a) { return __uint_as_float(a & 0xffff0000u); }

__device__ __forceinline__ uint4 ldg128(const void* p) {
  uint4 v;
  asm volatile("ld.global.nc.L1::no_allocate.v4.u32 {%0,%1,%2,%3}, [%4];"
               : "=r"(v.x), "=r"(v.y), "=r"(v.z), "=r"(v.w)
               : "l"(p));
  return v;
}
__device__ __forceinline__ uint2 ldg64(const void* p) {
  uint2 v;
  asm volatile("ld.global.nc.L1::no_allocate.v2.u32 {%0,%1}, [%2];" : "=r"(v.x), "=r"(v.y) : "l"(p));
  return v;
}
__device__ __forceinline__ void sts128(uint32_t a, uint32_t x, uint32_t y, uint32_t z, uint32_t w) {
  asm volatile("st.shared.v4.u32 [%0], {%1,%2,%3,%4};" ::"r"(a), "r"(x), "r"(y), "r"(z), "r"(w) : "memory");
}
__device__ __forceinline__ void sts24_pred(uint32_t a, const uint32_t (&v)[6], uint32_t pred) {
  asm volatile(
      "{\n.reg .pred p;\nsetp.ne.b32 p, %7, 0;\n"
      "@p st.shared.v4.u32 [%0], {%1,%2,%3,%4};\n"
      "@p st.shared.v2.u32 [%0+16], {%5,%6};\n}\n" ::"r"(a),
      "r"(v[0]), "r"(v[1]), "r"(v[2]), "r"(v[3]), "r"(v[4]), "r"(v[5]), "r"(pred)
      : "memory");
}
__device__ __forceinline__ uint4 lds128(uint32_t a) {
  uint4 v;
  asm volatile("ld.volatile.shared.v4.u32 {%0,%1,%2,%3}, [%4];" : "=r"(v.x), "=r"(v.y), "=r"(v.z), "=r"(v.w) : "r"(a) : "memory");
  return v;
}
__device__ __forceinline__ uint2 lds64(uint32_t a) {
  uint2 v;
  asm volatile("ld.volatile.shared.v2.u32 {%0,%1}, [%2];" : "=r"(v.x), "=r"(v.y) : "r"(a) : "memory");
  return v;
}
__device__ __forceinline__ void mbar_init(uint32_t bar, uint32_t cnt) {
  asm volatile("mbarrier.init.shared::cta.b64 [%0], %1;" ::"r"(bar), "r"(cnt) : "memory");
}
__device__ __forceinline__ void mbar_expect_tx(uint32_t bar, uint32_t bytes) {
  asm volatile("mbarrier.arrive.expect_tx.shared::cta.b64 _, [%0], %1;" ::"r"(bar), "r"(bytes) : "memory");
}
__device__ __forceinline__ void mbar_wait(uint32_t bar, uint32_t parity) {
  uint32_t ok;
  int it = 0;
  do {
    asm volatile(
        "{\n.reg .pred p;\n"
        "mbarrier.try_wait.parity.shared::cta.b64 p, [%1], %2;\n"
        "selp.u32 %0, 1, 0, p;\n}\n"
        : "=r"(ok)
        : "r"(bar), "r"(parity)
        : "memory");
    if (++it > (1 << 22)) __trap();
  } while (!ok);
}
__device__ __forceinline__ uint32_t mbar_try(uint32_t bar, uint32_t parity) {
  uint32_t ok;
  asm volatile(
      "{\n.reg .pred p;\n"
      "mbarrier.test_wait.parity.shared::cta.b64 p, [%1], %2;\n"
      "selp.u32 %0, 1, 0, p;\n}\n"
      : "=r"(ok)
      : "r"(bar), "r"(parity)
      : "memory");
  return ok;
}
__device__ __forceinline__ void mbar_arrive(uint32_t bar) {
  asm volatile("mbarrier.arrive.shared::cta.b64 _, [%0];" ::"r"(bar) : "memory");
}
__device__ __forceinline__ void mbar_arrive_remote(uint32_t rbar) {
  asm volatile("mbarrier.arrive.shared::cluster.b64 _, [%0];" ::"r"(rbar) : "memory");
}
__device__ __forceinline__ uint32_t mapa(uint32_t a, uint32_t rank) {
  uint32_t r;
  asm("mapa.shared::cluster.u32 %0, %1, %2;" : "=r"(r) : "r"(a), "r"(rank));
  return r;
}
__device__ __forceinline__ void st_async128(uint32_t ra, uint32_t x, uint32_t y, uint32_t z, uint32_t w, uint32_t rbar) {
  asm volatile("st.async.weak.shared::cluster.mbarrier::complete_tx::bytes.v4.b32 [%0], {%1,%2,%3,%4}, [%5];" ::"r"(ra),
               "r"(x), "r"(y), "r"(z), "r"(w), "r"(rbar)
               : "memory");
}
__device__ __forceinline__ void tma_row(uint32_t dst, const CUtensorMap* map, int grp, uint32_t bar) {
  asm volatile(
      "cp.async.bulk.tensor.5d.shared::cluster.global.mbarrier::complete_tx::bytes [%0], [%1, {%3, %3, %3, %4, %3}], "
      "[%2];" ::"r"(dst),
      "l"(map), "r"(bar), "r"(0), "r"(grp)
      : "memory");
}
__device__ __forceinline__ void tma_col(uint32_t dst, const CUtensorMap* map, int y, int x, uint32_t bar) {
  asm volatile(
      "cp.async.bulk.tensor.4d.shared::cluster.global.mbarrier::complete_tx::bytes [%0], [%1, {%3, %4, %3, %5}], "
      "[%2];" ::"r"(dst),
      "l"(map), "r"(bar), "r"(0), "r"(y), "r"(x)
      : "memory");
}
__device__ __forceinline__ void bulk_load(uint32_t dst, const void* src, uint32_t bytes, uint32_t bar) {
  asm volatile("cp.async.bulk.shared::cluster.global.mbarrier::complete_tx::bytes [%0], [%1], %2, [%3];" ::"r"(dst),
               "l"(src), "r"(bytes), "r"(bar)
               : "memory");
}
__device__ __forceinline__ void cluster_arrive() { asm volatile("barrier.cluster.arrive.relaxed.aligned;" ::: "memory"); }
__device__ __forceinline__ void cluster_wait() { asm volatile("barrier.cluster.wait.acquire.aligned;" ::: "memory"); }

__device__ __forceinline__ uint32_t wsel(const uint4& v, int i) { return i == 0 ? v.x : i == 1 ? v.y : i == 2 ? v.z : v.w; }
__device__ __forceinline__ int cmap(int j, int q, int e) { return j < 4 ? 8 * q + 2 * j + e : 32 + 4 * q + 2 * (j - 4) + e; }

struct DRow {
  uint32_t o0[6], o1[6];
};
struct PRow {
  uint4 a;
  uint2 b;
};
__device__ __forceinline__ uint32_t pw(const PRow& p, int j) {
  return j == 0 ? p.a.x : j == 1 ? p.a.y : j == 2 ? p.a.z : j == 3 ? p.a.w : j == 4 ? p.b.x : p.b.y;
}
template <bool ADD>
__device__ __forceinline__ uint32_t top(uint32_t a, uint32_t b) {
  return ADD ? hadd2(a, b) : hsub2(a, b);
}
template <bool ADD>
__device__ __forceinline__ void edges(uint32_t (&te)[6], uint32_t ra, uint32_t rb) {
  const uint4 a = lds128(ra), b = lds128(rb);
  const uint2 c = lds64(ra + 16), d = lds64(rb + 16);
  te[0] = top<ADD>(a.x, b.x);
  te[1] = top<ADD>(a.y, b.y);
  te[2] = top<ADD>(a.z, b.z);
  te[3] = top<ADD>(a.w, b.w);
  te[4] = top<ADD>(c.x, d.x);
  te[5] = top<ADD>(c.y, d.y);
}
template <bool ADD>
__device__ __forceinline__ void frags(uint32_t (&f)[12], const DRow& a, const DRow& b, const uint32_t (&te)[6], int ks,
                                      bool e0, bool e7) {
#pragma unroll
  for (int i = 0; i < 2; i++) {
    const int j = 2 * ks + i;
    const uint32_t t0 = top<ADD>(a.o0[j], b.o0[j]), t1 = top<ADD>(a.o1[j], b.o1[j]);
    const uint32_t nA = __shfl_up_sync(0xffffffffu, t1, 4);
    const uint32_t nB = __shfl_down_sync(0xffffffffu, t0, 4);
    f[0 + 2 * i] = e0 ? te[j] : nA;
    f[1 + 2 * i] = t0;
    f[4 + 2 * i] = t0;
    f[5 + 2 * i] = t1;
    f[8 + 2 * i] = t1;
    f[9 + 2 * i] = e7 ? te[j] : nB;
  }
}
template <int MODE>
__device__ __forceinline__ void fr1(uint32_t (&f)[12], const DRow& a, const DRow& b, int ks) {
#pragma unroll
  for (int i = 0; i < 2; i++) {
    const int j = 2 * ks + i;
    const uint32_t t0 = MODE == 0 ? a.o0[j] : top<MODE == 1>(a.o0[j], b.o0[j]);
    const uint32_t t1 = MODE == 0 ? a.o1[j] : top<MODE == 1>(a.o1[j], b.o1[j]);
    f[0 + 2 * i] = __shfl_up_sync(0xffffffffu, t1, 4);
    f[9 + 2 * i] = __shfl_down_sync(0xffffffffu, t0, 4);
    f[1 + 2 * i] = t0;
    f[4 + 2 * i] = t0;
    f[5 + 2 * i] = t1;
    f[8 + 2 * i] = t1;
  }
}
__device__ __forceinline__ void fr2(uint32_t (&f)[12], const uint32_t (&te)[6], int ks, bool e0, bool e7) {
#pragma unroll
  for (int i = 0; i < 2; i++) {
    f[0 + 2 * i] = e0 ? te[2 * ks + i] : f[0 + 2 * i];
    f[9 + 2 * i] = e7 ? te[2 * ks + i] : f[9 + 2 * i];
    asm volatile("" : "+r"(f[0 + 2 * i]), "+r"(f[9 + 2 * i]));
  }
}
struct ERaw {
  uint4 a, b;
  uint2 c, d;
};
__device__ __forceinline__ void ed1(ERaw& r, uint32_t ra, uint32_t rb) {
  r.a = lds128(ra);
  r.b = lds128(rb);
  r.c = lds64(ra + 16);
  r.d = lds64(rb + 16);
}
template <bool ADD>
__device__ __forceinline__ void ed2(uint32_t (&te)[6], const ERaw& r) {
  te[0] = top<ADD>(r.a.x, r.b.x);
  te[1] = top<ADD>(r.a.y, r.b.y);
  te[2] = top<ADD>(r.a.z, r.b.z);
  te[3] = top<ADD>(r.a.w, r.b.w);
  te[4] = top<ADD>(r.c.x, r.d.x);
  te[5] = top<ADD>(r.c.y, r.d.y);
}
template <int INIT>
__device__ __forceinline__ void conv_group(float (&acc)[48], const uint32_t (&f)[12], uint32_t dB, int pos, int ks) {
  wg_fence();
  wgmma_rs_n96<INIT>(acc, f[0], f[1], f[2], f[3], dB + (uint32_t)(((3 * pos + 0) * UT + 2 * ks * 1536) >> 4));
  wgmma_rs_n96<0>(acc, f[4], f[5], f[6], f[7], dB + (uint32_t)(((3 * pos + 1) * UT + 2 * ks * 1536) >> 4));
  wgmma_rs_n96<0>(acc, f[8], f[9], f[10], f[11], dB + (uint32_t)(((3 * pos + 2) * UT + 2 * ks * 1536) >> 4));
  wg_commit();
}
template <int CH, int INIT>
__device__ __forceinline__ void lateral(float (&acc)[24], uint32_t dA, uint32_t dwl) {
  wg_fence();
#pragma unroll
  for (int k = 0; k < 6; k++) {
    const uint32_t a = dA + (uint32_t)(((k >> 1) * CH + (k & 1) * 32) >> 4);
    const uint32_t b = dwl + (uint32_t)(k * 1536 >> 4);
    if (k == 0)
      wgmma_ss_n48<INIT>(acc, a, b);
    else
      wgmma_ss_n48<0>(acc, a, b);
  }
  wg_commit();
}

#define AI __attribute__((always_inline))
template <int V>
struct IC {
  static constexpr int value = V;
};

template <int RANK>
__device__ __forceinline__ void fpn_body(const CUtensorMap& map_row, const CUtensorMap& map_col,
                                         const __nv_bfloat16* __restrict__ p_coarse,
                                         const __nv_bfloat16* __restrict__ w_lat,
                                         const __nv_bfloat16* __restrict__ w_out, __nv_bfloat16* __restrict__ out) {
  extern __shared__ __align__(1024) unsigned char smem[];
  const uint32_t sb = (uint32_t)__cvta_generic_to_shared(smem);
  if ((sb & 0xFFFFFFu) != SB0) __trap();
  const int tid = threadIdx.x;
  const int wg = __shfl_sync(0xffffffffu, tid >> 7, 0);
  const int t128 = tid & 127;
  const int w = __shfl_sync(0xffffffffu, (tid >> 5) & 3, 0);
  const int lane = tid & 31;
  const int g = lane >> 2, q = lane & 3;
  constexpr uint32_t rank = RANK;
  const int cl = blockIdx.x >> 1;
  const int y0 = (cl >> 2) * 32;
  const int x0 = ((cl & 3) * 2 + wg) * 64;

  if (tid == 0) {
#pragma unroll
    for (int i = 0; i < 2; i++) {
      const uint32_t b = sb + OFF_BAR + i * 64;
      mbar_init(b + 0, 1);
      mbar_init(b + 8, 1);
      mbar_init(b + 16, 1);
      mbar_init(b + 24, 1);
      mbar_init(b + 32, 4);
      mbar_init(b + 40, 4);
      mbar_init(b + 48, 1);
      mbar_init(b + 56, 4);
      mbar_init(sb + OFF_BAR + 128 + i * 16, 1);
      mbar_init(sb + OFF_BAR + 136 + i * 16, 1);
    }
    asm volatile("fence.mbarrier_init.release.cluster;" ::: "memory");
    fence_async_smem();
#pragma unroll
    for (int i = 0; i < 2; i++) {
      const uint32_t b = sb + OFF_BAR + i * 64;
      const int xw = ((cl & 3) * 2 + i) * 64;
      mbar_expect_tx(b + 48, 2 * HTILE);
      tma_col(sb + OFF_X + i * X_BYTES, &map_col, y0 - 1, xw - 1, b + 48);
      tma_col(sb + OFF_X + i * X_BYTES + HTILE, &map_col, y0 - 1, xw + 64, b + 48);
      mbar_expect_tx(b + 0, 2 * CSLOT);
      tma_row(sb + OFF_C + i * 2 * CSLOT, &map_row, (y0 - 1) * 32 + (xw >> 4), b + 0);
      tma_row(sb + OFF_H + i * HE_BYTES, &map_row, (y0 + 1) * 32 + (xw >> 4), b + 0);
      mbar_expect_tx(b + 8, CSLOT);
      tma_row(sb + OFF_C + i * 2 * CSLOT + CSLOT, &map_row, y0 * 32 + (xw >> 4), b + 8);
      mbar_expect_tx(b + 16, XROW);
      mbar_expect_tx(b + 24, XROW);
    }
  }
  cluster_arrive();

  const unsigned char* pc = (const unsigned char*)p_coarse + 96 * rank;

  PRow hp[2][2], pA, pp;
  bool hv[2][2];
#pragma unroll
  for (int sd = 0; sd < 2; sd++)
#pragma unroll
    for (int h = 0; h < 2; h++) {
      const int hr = 16 * w + 8 * h + g, yy = y0 - 1 + hr, xx = sd ? x0 + 64 : x0 - 1;
      hv[sd][h] = hr < 34 && yy >= 0 && yy < IMG && xx >= 0 && xx < IMG;
      const unsigned char* a = pc + (hv[sd][h] ? ((size_t)(yy >> 1) * 256 + (xx >> 1)) * 192 : 0);
      hp[sd][h].a = ldg128(a + 16 * q);
      hp[sd][h].b = ldg64(a + 64 + 8 * q);
    }
  uint32_t poff = ((y0 >> 1) * 256 + (x0 >> 1) + 8 * w + g) * 192 + 16 * q;
  {
    const unsigned char* a = pc + poff - (y0 > 0 ? 49152 : 0);
    pA.a = ldg128(a);
    pA.b = ldg64(a + 64 - 8 * q);
    pp.a = ldg128(pc + poff);
    pp.b = ldg64(pc + poff + 64 - 8 * q);
    poff += 49152;
  }

  uint32_t ticket = 0;
  if (tid >= 224) {
    const int idx = blockIdx.x * 14 + lane;
    if (lane < 14 && idx < 1728) {
      const int wd = idx & 3, t = idx >> 2, rk = t / 216, rem = t % 216, dj = rem / 72, kc = (rem % 72) / 12, u = rem % 12;
      const unsigned char* src = (const unsigned char*)w_out + ((size_t)(dj * 96 + 48 * rk) * 96 + 8 * u) * 2 + 4 * wd;
      uint32_t v[3][8];
#pragma unroll
      for (int kk = 0; kk < 8; kk++) {
        const int ci = cmap(kc, kk >> 1, kk & 1);
#pragma unroll
        for (int di = 0; di < 3; di++) v[di][kk] = __ldg((const uint32_t*)(src + (size_t)di * 3 * 96 * 192 + ci * 192));
      }
      uint32_t u0[2][4], u1[2][4], u2[2][4], u3[2][4];
#pragma unroll
      for (int kp = 0; kp < 4; kp++) {
        const uint32_t a0 = v[0][2 * kp], a1 = v[0][2 * kp + 1];
        const uint32_t b0 = v[1][2 * kp], b1 = v[1][2 * kp + 1];
        const uint32_t c0 = v[2][2 * kp], c1 = v[2][2 * kp + 1];
        u0[0][kp] = __byte_perm(a0, a1, 0x5410);
        u0[1][kp] = __byte_perm(a0, a1, 0x7632);
        u3[0][kp] = __byte_perm(c0, c1, 0x5410);
        u3[1][kp] = __byte_perm(c0, c1, 0x7632);
        const float s0l = bf_lo(a0) + bf_lo(c0), s1l = bf_lo(a1) + bf_lo(c1);
        const float s0h = bf_hi(a0) + bf_hi(c0), s1h = bf_hi(a1) + bf_hi(c1);
        u1[0][kp] = pack_bf16((s0l + bf_lo(b0)) * 0.5f, (s1l + bf_lo(b1)) * 0.5f);
        u1[1][kp] = pack_bf16((s0h + bf_hi(b0)) * 0.5f, (s1h + bf_hi(b1)) * 0.5f);
        u2[0][kp] = pack_bf16((s0l - bf_lo(b0)) * 0.5f, (s1l - bf_lo(b1)) * 0.5f);
        u2[1][kp] = pack_bf16((s0h - bf_hi(b0)) * 0.5f, (s1h - bf_hi(b1)) * 0.5f);
      }
      unsigned char* dst = g_u + rk * 12 * UT + dj * UT + kc * 1536 + (32 * (u >> 2) + 2 * (u & 3) + 8 * wd) * 16;
#pragma unroll
      for (int e = 0; e < 2; e++) {
        *(uint4*)(dst + e * 16) = make_uint4(u0[e][0], u0[e][1], u0[e][2], u0[e][3]);
        *(uint4*)(dst + e * 16 + 3 * UT) = make_uint4(u1[e][0], u1[e][1], u1[e][2], u1[e][3]);
        *(uint4*)(dst + e * 16 + 6 * UT) = make_uint4(u2[e][0], u2[e][1], u2[e][2], u2[e][3]);
        *(uint4*)(dst + e * 16 + 9 * UT) = make_uint4(u3[e][0], u3[e][1], u3[e][2], u3[e][3]);
      }
      asm volatile("fence.proxy.async.global;" ::: "memory");
    }
    __syncwarp();
    if (lane == 0) asm volatile("atom.release.gpu.global.add.u32 %0, [%1], 1;" : "=r"(ticket) : "l"(&g_cnt) : "memory");
  } else if (tid >= 32 && tid < 104) {
    {
      const int blk = tid - 32;
      const int kc = blk / 6, u = blk % 6;
      uint4 v[8];
#pragma unroll
      for (int kk = 0; kk < 8; kk++)
        v[kk] = ldg128((const unsigned char*)w_lat + ((size_t)(8 * kc + kk) * 96 + 48 * rank + 8 * u) * 2);
#pragma unroll
      for (int wd = 0; wd < 4; wd++) {
        const int n = u < 4 ? 8 * wd + 2 * u : 8 * (4 + (wd & 1)) + 2 * (2 * (u - 4) + (wd >> 1));
        const uint32_t a = sb + OFF_WL + kc * 768 + n * 16;
        uint32_t lo[4], hi[4];
#pragma unroll
        for (int kp = 0; kp < 4; kp++) {
          lo[kp] = __byte_perm(wsel(v[2 * kp], wd), wsel(v[2 * kp + 1], wd), 0x5410);
          hi[kp] = __byte_perm(wsel(v[2 * kp], wd), wsel(v[2 * kp + 1], wd), 0x7632);
        }
        sts128(a, lo[0], lo[1], lo[2], lo[3]);
        sts128(a + 16, hi[0], hi[1], hi[2], hi[3]);
      }
    }
  }
  fence_async_smem();
  __syncthreads();
  cluster_wait();

  const uint32_t bb = sb + OFF_BAR + wg * 64;
  constexpr uint32_t dwl = make_desc(SB0 + OFF_WL, 768);
  constexpr uint32_t dB = make_desc(SB0 + OFF_U, 1536);
  const uint32_t cs = sb + OFF_C + wg * 2 * CSLOT;
  const uint32_t dC = make_desc(SB0 + OFF_C, 16) + wg * (2 * CSLOT >> 4);
  const uint32_t xbase = sb + OFF_X + wg * X_BYTES;
  const uint32_t dH = make_desc(SB0 + OFF_X, 16) + wg * (X_BYTES >> 4);
  const uint32_t hb = sb + OFF_H + wg * HE_BYTES;
  const uint32_t eb = hb + H_BYTES;
  const uint32_t ub = sb + OFF_BAR + 128;
  const uint32_t xa = xbase + t128 * 16;
  const uint32_t peer = rank ^ 1;
  const uint32_t rdelta = __shfl_sync(0xffffffffu, mapa(bb, peer) - bb, 0);
#define r_xa (xa + rdelta)
#define r_bb (bb + rdelta)
  const int grp0 = (y0 - 1) * 32 + (x0 >> 4);
  const bool last_block = (y0 + 32 == IMG);

  const bool e0 = g == 0, e7 = g == 7;
  const bool halo_lane = (w == 0 && g < 4) || (w == 3 && g >= 4);
  const uint32_t ewr = eb + (2 * w + (e7 ? 1 : 0)) * 512 + 32 * q;
  const uint32_t erd =
      (halo_lane ? (g < 4 ? hb : hb + HSIDE) : (g < 4 ? eb + (2 * w - 1) * 512 : eb + (2 * w + 2) * 512)) + 32 * q;
  const uint32_t emask = halo_lane ? 0xFFFFu : 511u;
  auto er = [&](int k) AI { return erd + (((uint32_t)k << 8) & emask); };

  float ax[48], ay[48], lat[24];
  DRow d1, d2, t0, t3;
  uint32_t f0[12], f1[12], f2[12], te[6], kp[12];
#pragma unroll
  for (int i = 0; i < 12; i++) kp[i] = 0;

  auto d_pack = [&](auto MODE, int i, DRow& d, DRow& t, const float(&acc)[24], const PRow& p, bool zero) AI {
    constexpr int mode = decltype(MODE)::value;
#pragma unroll
    for (int j = 0; j < 6; j++) {
      uint32_t n0 = hadd2(pack_bf16(acc[4 * j], acc[4 * j + 1]), pw(p, j));
      uint32_t n1 = hadd2(pack_bf16(acc[4 * j + 2], acc[4 * j + 3]), pw(p, j));
      if (zero) n0 = n1 = 0;
      if (mode == 1) {
        t.o0[j] = hsub2(n0, d.o0[j]);
        t.o1[j] = hsub2(n1, d.o1[j]);
      }
      if (mode == 2) {
        t.o0[j] = hsub2(d.o0[j], n0);
        t.o1[j] = hsub2(d.o1[j], n1);
      }
      d.o0[j] = n0;
      d.o1[j] = n1;
    }
    uint32_t ev[6];
#pragma unroll
    for (int j = 0; j < 6; j++) ev[j] = e0 ? d.o0[j] : d.o1[j];
    sts24_pred(ewr + (i & 3) * 128, ev, e0 || e7);
    if (mode != 0) {
      __syncwarp();
      if (lane == 0) mbar_arrive(bb + 56);
    }
  };
  auto refill = [&](int i) AI {
    if (t128 == 0 && i + 2 <= 33) {
      mbar_expect_tx(bb + (i & 1) * 8, CSLOT);
      tma_row(cs + (i & 1) * CSLOT, &map_row, grp0 + (i + 2) * 32, bb + (i & 1) * 8);
    }
  };
  auto send = [&](const float(&acc)[48], int b) AI {
    constexpr int rk = RANK;
#pragma unroll
    for (int J = 0; J < 3; J++) {
      uint32_t sd[4];
#pragma unroll
      for (int i = 0; i < 4; i++) {
        const int j = 4 * J + i;
        sd[i] = pack_bf16(acc[4 * j + 2 - 2 * rk], acc[4 * j + 3 - 2 * rk]);
        kp[j] = pack_bf16(acc[4 * j + 2 * rk], acc[4 * j + 2 * rk + 1]);
      }
      st_async128(r_xa + b * XROW + J * 2048, sd[0], sd[1], sd[2], sd[3], r_bb + 16 + 8 * b);
    }
  };
  uint32_t ooff = ((y0 * IMG) + x0 + 16 * w + 2 * g + rank) * 192 + 16 * q;
  uint4 xr[3];
  auto fin1 = [&](int b) AI {
#pragma unroll
    for (int J = 0; J < 3; J++) xr[J] = lds128(xa + b * XROW + J * 2048);
  };
  auto fin2 = [&](int b, uint32_t parity, uint32_t ok, bool more) AI {
    if (!ok) {
      mbar_wait(bb + 16 + 8 * b, parity);
      fin1(b);
    }
    if (more && t128 == 0) mbar_expect_tx(bb + 16 + 8 * b, XROW);
#pragma unroll
    for (int J = 0; J < 3; J++) {
      uint4 o;
      o.x = hadd2(kp[4 * J + 0], xr[J].x);
      o.y = hadd2(kp[4 * J + 1], xr[J].y);
      o.z = hadd2(kp[4 * J + 2], xr[J].z);
      o.w = hadd2(kp[4 * J + 3], xr[J].w);
      *(uint4*)((unsigned char*)out + (ooff + 64 * J)) = o;
    }
    ooff += 98304;
    __syncwarp();
    if (more && lane == 0) mbar_arrive_remote(r_bb + 32 + 8 * b);
  };

  {
    float lat2[24], lr0[24], lr1[24], lr2[24];
    mbar_wait(bb + 48, 0);
    lateral<2560, 1>(lat, dH, dwl);
    lateral<2560, 1>(lat2, dH + (HTILE >> 4), dwl);
    mbar_wait(bb + 8, 0);
    lateral<4096, 1>(lr1, dC + (CSLOT >> 4), dwl);
    mbar_wait(bb + 0, 0);
    lateral<4096, 1>(lr0, dC, dwl);
    lateral<4096, 1>(lr2, make_desc(SB0 + OFF_H, 16) + wg * (HE_BYTES >> 4), dwl);
    if (tid == 224) {
      const uint32_t target = (ticket | 127u) + 1u;
      uint32_t c, n = 0;
      do {
        asm volatile("ld.acquire.gpu.global.u32 %0, [%1];" : "=r"(c) : "l"(&g_cnt) : "memory");
        if (++n > (1u << 22)) __trap();
      } while ((int)(c - target) < 0);
      asm volatile("fence.proxy.async.global;" ::: "memory");
#pragma unroll
      for (int i = 0; i < 4; i++) {
        const int pos = i == 0 ? 1 : i == 1 ? 2 : i == 2 ? 0 : 3;
        mbar_expect_tx(ub + 8 * pos, 3 * UT);
        bulk_load(sb + OFF_U + pos * 3 * UT, g_u + (rank * 12 + pos * 3) * UT, 3 * UT, ub + 8 * pos);
      }
    }
    __syncwarp();
    wg_wait<0>();
    fence_regs(lat);
    fence_regs(lat2);
    fence_regs(lr0);
    fence_regs(lr1);
    fence_regs(lr2);
    asm volatile("bar.sync %0, 128;" ::"r"(wg + 1) : "memory");
    refill(1);
    refill(2);
    __syncwarp();
    if (lane == 0) {
      mbar_arrive_remote(r_bb + 32);
      mbar_arrive_remote(r_bb + 40);
    }
#pragma unroll
    for (int h = 0; h < 2; h++) {
      const int hr = 16 * w + 8 * h + g;
      uint32_t v0[6], v1[6];
#pragma unroll
      for (int j = 0; j < 6; j++) {
        v0[j] = hv[0][h] ? hadd2(pack_bf16(lat[4 * j + 2 * h], lat[4 * j + 2 * h + 1]), pw(hp[0][h], j)) : 0u;
        v1[j] = hv[1][h] ? hadd2(pack_bf16(lat2[4 * j + 2 * h], lat2[4 * j + 2 * h + 1]), pw(hp[1][h], j)) : 0u;
      }
      sts24_pred(hb + hr * 128 + 32 * q, v0, hr < 34);
      sts24_pred(hb + HSIDE + hr * 128 + 32 * q, v1, hr < 34);
    }
    d_pack(IC<0>{}, 0, d2, t0, lr0, pA, y0 == 0);
    d_pack(IC<0>{}, 1, d1, t3, lr1, pp, false);
    d_pack(IC<2>{}, 2, d2, t0, lr2, pp, false);
    mbar_wait(bb + 56, 0);
    pp.a = ldg128(pc + poff);
    pp.b = ldg64(pc + poff + 64 - 8 * q);
    edges<true>(te, er(0) + 128, er(1));
    frags<true>(f0, d1, d2, te, 0, e0, e7);
    mbar_wait(ub + 8, 0);
    conv_group<1>(ax, f0, dB, 1, 0);
    frags<true>(f1, d1, d2, te, 1, e0, e7);
  }

  ERaw er4;
  uint32_t ok1, ok2;
#define CUT sched_cut<__LINE__>(cl)
  auto stepA = [&](auto FIRST, int s) AI {
    constexpr bool notfirst = !decltype(FIRST)::value;
    const uint32_t par = s & 1;
    wg_wait<1>();
    if (notfirst) fence_regs(ay);
    CUT;
    fr1<1>(f2, d1, d2, 2);
    if (notfirst) {
      ok1 = mbar_try(bb + 16, par ^ 1);
      fin1(0);
    }
    CUT;
    conv_group<0>(ax, f1, dB, 1, 1);
    CUT;
    if (notfirst) fin2(0, par ^ 1, ok1, true);
    fr2(f2, te, 2, e0, e7);
    wg_wait<1>();
    CUT;
    ed1(er4, er(s + 1), er(s) + 128);
    fr1<2>(f0, d2, d1, 0);
    if (notfirst) ok2 = mbar_try(bb + 40, par ^ 1);
    CUT;
    conv_group<0>(ax, f2, dB, 1, 2);
    CUT;
    if (notfirst) {
      if (!ok2) mbar_wait(bb + 40, par ^ 1);
      send(ay, 1);
    }
    ed2<false>(te, er4);
    fr2(f0, te, 0, e0, e7);
    wg_wait<1>();
    CUT;
    fr1<2>(f1, d2, d1, 1);
    if (!notfirst) mbar_wait(ub + 16, 0);
    CUT;
    conv_group<notfirst ? 2 : 1>(ay, f0, dB, 2, 0);
    CUT;
    fr2(f1, te, 1, e0, e7);
    wg_wait<1>();
    CUT;
    fr1<2>(f2, d2, d1, 2);
    CUT;
    conv_group<0>(ay, f1, dB, 2, 1);
    CUT;
    fr2(f2, te, 2, e0, e7);
    wg_wait<1>();
    CUT;
    ed1(er4, er(s), er(s + 1));
    fr1<0>(f0, t0, t0, 0);
    ok1 = mbar_try(bb + 8, par ^ 1);
    CUT;
    conv_group<0>(ay, f2, dB, 2, 2);
    CUT;
    ed2<false>(te, er4);
    fr2(f0, te, 0, e0, e7);
    if (!ok1) mbar_wait(bb + 8, par ^ 1);
    wg_wait<1>();
    CUT;
    fr1<0>(f1, t0, t0, 1);
    CUT;
    lateral<4096, 2>(lat, dC + (CSLOT >> 4), dwl);
    CUT;
    fr2(f1, te, 1, e0, e7);
    if (!notfirst) {
      mbar_wait(ub + 0, 0);
      mbar_wait(ub + 24, 0);
    }
    CUT;
    wg_wait<1>();
    fence_regs(ax);
    fence_regs(ay);
  };
  auto stepB = [&](auto LAST, int s) AI {
    constexpr bool notlast = !decltype(LAST)::value;
    const uint32_t par = s & 1;
    fr1<0>(f2, t0, t0, 2);
    if (notlast) ok2 = mbar_try(bb + 0, par ^ 1);
    CUT;
#pragma unroll
    for (int i = 0; i < 48; i++) {
      asm volatile("add.f32 %0, %0, %1;\n\tfma.rn.f32 %1, %1, 0fC0000000, %0;" : "+f"(ax[i]), "+f"(ay[i]));
    }
    fence_regs(ax);
    fence_regs(ay);
    conv_group<0>(ax, f0, dB, 0, 0);
    wg_wait<1>();
    fence_regs(lat);
    CUT;
    d_pack(IC<1>{}, 2 * s + 3, d1, t3, lat, pp, last_block && !notlast);
    fr2(f2, te, 2, e0, e7);
    if (notlast && !ok2) mbar_wait(bb + 0, par ^ 1);
    ok1 = mbar_try(bb + 24, par ^ 1);
    fin1(1);
    CUT;
    if (notlast) lateral<4096, 2>(lat, dC, dwl);
    CUT;
    if (s > 0) fin2(1, par ^ 1, ok1, true);
    wg_wait<notlast ? 1 : 0>();
    CUT;
    ok1 = mbar_try(bb + 56, 1);
    ed1(er4, er(s + 1) + 128, er(s) + 128);
    fr1<0>(f0, t3, t3, 0);
    CUT;
    conv_group<0>(ax, f1, dB, 0, 1);
    CUT;
    if (!ok1) {
      mbar_wait(bb + 56, 1);
      ed1(er4, er(s + 1) + 128, er(s) + 128);
    }
    refill(2 * s + 3);
    ed2<false>(te, er4);
    fr2(f0, te, 0, e0, e7);
    if (notlast) {
      wg_wait<1>();
      fence_regs(lat);
      CUT;
      d_pack(IC<2>{}, 2 * s + 4, d2, t0, lat, pp, false);
      if ((y0 >> 1) + s + 2 < 256) poff += 49152;
      pp.a = ldg128(pc + poff);
      pp.b = ldg64(pc + poff + 64 - 8 * q);
    }
    CUT;
    conv_group<0>(ax, f2, dB, 0, 2);
    wg_wait<1>();
    keep(f1);
    CUT;
    fr1<0>(f1, t3, t3, 1);
    if (notlast) ok1 = mbar_try(bb + 56, 0);
    CUT;
    conv_group<0>(ay, f0, dB, 3, 0);
    CUT;
    fr2(f1, te, 1, e0, e7);
    if (notlast) {
      if (!ok1) mbar_wait(bb + 56, 0);
      refill(2 * s + 4);
    }
    wg_wait<1>();
    fence_regs(ax);
    keep(f2);
    CUT;
    fr1<0>(f2, t3, t3, 2);
    ok2 = mbar_try(bb + 32, par);
    CUT;
    conv_group<0>(ay, f1, dB, 3, 1);
    CUT;
    if (!ok2) mbar_wait(bb + 32, par);
    send(ax, 0);
    fr2(f2, te, 2, e0, e7);
    if (notlast) {
      wg_wait<1>();
      CUT;
      ed1(er4, er(s + 1) + 128, er(s + 2));
      fr1<1>(f0, d1, d2, 0);
    }
    CUT;
    conv_group<0>(ay, f2, dB, 3, 2);
    if (notlast) {
      CUT;
      ed2<true>(te, er4);
      fr2(f0, te, 0, e0, e7);
      wg_wait<1>();
      CUT;
      fr1<1>(f1, d1, d2, 1);
      CUT;
      conv_group<2>(ax, f0, dB, 1, 0);
      CUT;
      fr2(f1, te, 1, e0, e7);
    }
  };

  stepA(IC<1>{}, 0);
#pragma unroll 1
  for (int s = 0; s < NSTEP - 1; s++) {
    stepB(IC<0>{}, s);
    stepA(IC<0>{}, s + 1);
  }
  stepB(IC<1>{}, NSTEP - 1);
  fin2(0, 1, 0, false);
  wg_wait<0>();
  fence_regs(ay);
  mbar_wait(bb + 40, 1);
  send(ay, 1);
  fin2(1, 1, 0, false);
}

__global__ void __cluster_dims__(2, 1, 1) __launch_bounds__(256, 1)
    fpn_kernel(const __grid_constant__ CUtensorMap map_row, const __grid_constant__ CUtensorMap map_col,
               const __nv_bfloat16* __restrict__ p_coarse, const __nv_bfloat16* __restrict__ w_lat,
               const __nv_bfloat16* __restrict__ w_out, __nv_bfloat16* __restrict__ out) {
  uint32_t rank;
  asm("mov.u32 %0, %%cluster_ctarank;" : "=r"(rank));
  if (rank)
    fpn_body<1>(map_row, map_col, p_coarse, w_lat, w_out, out);
  else
    fpn_body<0>(map_row, map_col, p_coarse, w_lat, w_out, out);
}

typedef CUresult (*EncodeFn)(CUtensorMap*, CUtensorMapDataType, cuuint32_t, void*, const cuuint64_t*, const cuuint64_t*,
                             const cuuint32_t*, const cuuint32_t*, CUtensorMapInterleave, CUtensorMapSwizzle,
                             CUtensorMapL2promotion, CUtensorMapFloatOOBfill);

}

extern "C" void kernel_launch(void* const* d_in, const int* in_sizes, int n_in, void* d_out, int out_size) {
  (void)in_sizes;
  (void)n_in;
  (void)out_size;
  static EncodeFn encode = nullptr;
  if (!encode) {
    cudaFuncSetAttribute(fpn_kernel, cudaFuncAttributeMaxDynamicSharedMemorySize, SMEM_BYTES);
    void* fn = nullptr;
    cudaDriverEntryPointQueryResult st;
    cudaGetDriverEntryPoint("cuTensorMapEncodeTiled", &fn, cudaEnableDefault, &st);
    encode = (EncodeFn)fn;
  }
  CUtensorMap map_row, map_col;
  {
    const cuuint64_t dim[5] = {32, 8, 2, 16384, 3};
    const cuuint64_t str[4] = {384, 192, 3072, 64};
    const cuuint32_t box[5] = {32, 8, 2, 4, 3};
    const cuuint32_t es[5] = {1, 1, 1, 1, 1};
    encode(&map_row, CU_TENSOR_MAP_DATA_TYPE_BFLOAT16, 5, d_in[0], dim, str, box, es, CU_TENSOR_MAP_INTERLEAVE_NONE,
           CU_TENSOR_MAP_SWIZZLE_64B, CU_TENSOR_MAP_L2_PROMOTION_L2_256B, CU_TENSOR_MAP_FLOAT_OOB_FILL_NONE);
  }
  {
    const cuuint64_t dim[4] = {32, 512, 3, 512};
    const cuuint64_t str[3] = {98304, 64, 192};
    const cuuint32_t box[4] = {32, 40, 3, 1};
    const cuuint32_t es[4] = {1, 1, 1, 1};
    encode(&map_col, CU_TENSOR_MAP_DATA_TYPE_BFLOAT16, 4, d_in[0], dim, str, box, es, CU_TENSOR_MAP_INTERLEAVE_NONE,
           CU_TENSOR_MAP_SWIZZLE_64B, CU_TENSOR_MAP_L2_PROMOTION_L2_128B, CU_TENSOR_MAP_FLOAT_OOB_FILL_NONE);
  }
  fpn_kernel<<<128, 256, SMEM_BYTES, cudaStreamPerThread>>>(map_row, map_col, (const __nv_bfloat16*)d_in[1],
                                                            (const __nv_bfloat16*)d_in[2], (const __nv_bfloat16*)d_in[3],
                                                            (__nv_bfloat16*)d_out);
}
```

```cpp
#include <cuda_runtime.h>
#include <cuda.h>
#include <cuda_bf16.h>
#include <stdint.h>

namespace {

constexpr int IMG = 512;
constexpr int CSLOT = 12288;
constexpr int UT = 9216;
constexpr int OFF_C = 0;
constexpr int OFF_U = 4 * CSLOT;
constexpr int OFF_WL = OFF_U + 12 * UT;
constexpr int OFF_X = OFF_WL + 9216;
constexpr int XROW = 6144;
constexpr int HTILE = 7680;
constexpr int X_BYTES = 2 * HTILE;
constexpr int OFF_H = OFF_X + 2 * X_BYTES;
constexpr int HSIDE = 35 * 128;
constexpr int H_BYTES = 2 * HSIDE;
constexpr int HE_BYTES = 13312;
constexpr int OFF_BAR = OFF_H + 2 * HE_BYTES;
constexpr int SMEM_BYTES = OFF_BAR + 192;
__device__ __align__(1024) unsigned char g_u[2 * 12 * UT];
__device__ unsigned int g_cnt;
constexpr int NSTEP = 16;

#define R4(c, a, o) c(a[o]), c(a[o + 1]), c(a[o + 2]), c(a[o + 3])
#define R8(c, a, o) R4(c, a, o), R4(c, a, o + 4)
#define R24(c, a, o) R8(c, a, o), R8(c, a, o + 8), R8(c, a, o + 16)
#define RL24 \
  "%0, %1, %2, %3, %4, %5, %6, %7, %8, %9, %10, %11, %12, %13, %14, %15, %16, %17, %18, %19, %20, %21, %22, %23"
#define RL48                                                                                                       \
  RL24 ", %24, %25, %26, %27, %28, %29, %30, %31, %32, %33, %34, %35, %36, %37, %38, %39, %40, %41, %42, %43, %44, " \
       "%45, %46, %47"

constexpr uint32_t HI_W = 128 >> 4;
constexpr uint32_t HI_C = (512 >> 4) | (2u << 30);
template <int INIT>
__device__ __forceinline__ void wgmma_rs_n96(float (&d)[48], uint32_t a0, uint32_t a1, uint32_t a2, uint32_t a3,
                                             uint32_t db) {
  if constexpr (INIT == 1) {
    asm volatile(
        "{\n.reg .pred p;\n.reg .b64 db;\nsetp.ne.b32 p, 0, 0;\nmov.b64 db, {%52, %53};\n"
        "wgmma.mma_async.sync.aligned.m64n96k16.f32.bf16.bf16 {" RL48 "}, {%48, %49, %50, %51}, db, p, 1, 1, 0;\n}\n"
        : R24("=f", d, 0), R24("=f", d, 24)
        : "r"(a0), "r"(a1), "r"(a2), "r"(a3), "r"(db), "n"(HI_W));
  } else {
    asm volatile(
        "{\n.reg .pred p;\n.reg .b64 db;\nsetp.eq.b32 p, %54, 0;\nmov.b64 db, {%52, %53};\n"
        "wgmma.mma_async.sync.aligned.m64n96k16.f32.bf16.bf16 {" RL48 "}, {%48, %49, %50, %51}, db, p, 1, 1, 0;\n}\n"
        : R24("+f", d, 0), R24("+f", d, 24)
        : "r"(a0), "r"(a1), "r"(a2), "r"(a3), "r"(db), "n"(HI_W), "n"(INIT));
  }
}
template <int INIT>
__device__ __forceinline__ void wgmma_ss_n48(float (&d)[24], uint32_t da, uint32_t db) {
  if constexpr (INIT == 1) {
    asm volatile(
        "{\n.reg .pred p;\n.reg .b64 da, db;\nsetp.ne.b32 p, 0, 0;\nmov.b64 da, {%24, %26};\nmov.b64 db, {%25, %27};\n"
        "wgmma.mma_async.sync.aligned.m64n48k16.f32.bf16.bf16 {" RL24 "}, da, db, p, 1, 1, 0, 0;\n}\n"
        : R24("=f", d, 0)
        : "r"(da), "r"(db), "n"(HI_C), "n"(HI_W));
  } else {
    asm volatile(
        "{\n.reg .pred p;\n.reg .b64 da, db;\nsetp.eq.b32 p, %28, 0;\nmov.b64 da, {%24, %26};\nmov.b64 db, {%25, %27};\n"
        "wgmma.mma_async.sync.aligned.m64n48k16.f32.bf16.bf16 {" RL24 "}, da, db, p, 1, 1, 0, 0;\n}\n"
        : R24("+f", d, 0)
        : "r"(da), "r"(db), "n"(HI_C), "n"(HI_W), "n"(INIT));
  }
}
__device__ __forceinline__ void wg_fence() { asm volatile("wgmma.fence.sync.aligned;" ::: "memory"); }
__device__ __forceinline__ void wg_commit() { asm volatile("wgmma.commit_group.sync.aligned;" ::: "memory"); }
template <int K>
__device__ __forceinline__ void sched_cut(uint32_t x) {
  asm volatile("{\n.reg .pred p;\nsetp.eq.u32 p, %0, %1;\n@p trap;\n}\n" ::"r"(x), "n"(100000 + K) : "memory");
}
template <int N>
__device__ __forceinline__ void wg_wait() {
  asm volatile("wgmma.wait_group.sync.aligned %0;" ::"n"(N) : "memory");
}
template <int N>
__device__ __forceinline__ void fence_regs(float (&a)[N]) {
#pragma unroll
  for (int i = 0; i < N; i++) asm volatile("" : "+f"(a[i])::"memory");
}
constexpr uint32_t SB0 = 0x400;
__host__ __device__ constexpr uint32_t make_desc(uint32_t saddr, uint32_t lbo) {
  return ((saddr & 0x3FFFF) >> 4) | ((lbo >> 4) << 16);
}
__device__ __forceinline__ void fence_async_smem() { asm volatile("fence.proxy.async.shared::cta;" ::: "memory"); }
__device__ __forceinline__ void keep(const uint32_t (&f)[12]) {
#pragma unroll
  for (int i = 0; i < 12; i++) asm volatile("" ::"r"(f[i]) : "memory");
}

__device__ __forceinline__ uint32_t pack_bf16(float lo, float hi) {
  uint32_t r;
  asm("cvt.rn.bf16x2.f32 %0, %1, %2;" : "=r"(r) : "f"(hi), "f"(lo));
  return r;
}
__device__ __forceinline__ uint32_t hadd2(uint32_t a, uint32_t b) {
  uint32_t r;
  asm("add.rn.bf16x2 %0, %1, %2;" : "=r"(r) : "r"(a), "r"(b));
  return r;
}
__device__ __forceinline__ uint32_t hsub2(uint32_t a, uint32_t b) {
  uint32_t r;
  asm("sub.rn.bf16x2 %0, %1, %2;" : "=r"(r) : "r"(a), "r"(b));
  return r;
}
__device__ __forceinline__ float bf_lo(uint32_t a) { return __uint_as_float(a << 16); }
__device__ __forceinline__ float bf_hi(uint32_t a) { return __uint_as_float(a & 0xffff0000u); }

__device__ __forceinline__ uint4 ldg128(const void* p) {
  uint4 v;
  asm volatile("ld.global.nc.L1::no_allocate.v4.u32 {%0,%1,%2,%3}, [%4];"
               : "=r"(v.x), "=r"(v.y), "=r"(v.z), "=r"(v.w)
               : "l"(p));
  return v;
}
__device__ __forceinline__ uint2 ldg64(const void* p) {
  uint2 v;
  asm volatile("ld.global.nc.L1::no_allocate.v2.u32 {%0,%1}, [%2];" : "=r"(v.x), "=r"(v.y) : "l"(p));
  return v;
}
__device__ __forceinline__ void sts128(uint32_t a, uint32_t x, uint32_t y, uint32_t z, uint32_t w) {
  asm volatile("st.shared.v4.u32 [%0], {%1,%2,%3,%4};" ::"r"(a), "r"(x), "r"(y), "r"(z), "r"(w) : "memory");
}
__device__ __forceinline__ void sts24_pred(uint32_t a, const uint32_t (&v)[6], uint32_t pred) {
  asm volatile(
      "{\n.reg .pred p;\nsetp.ne.b32 p, %7, 0;\n"
      "@p st.shared.v4.u32 [%0], {%1,%2,%3,%4};\n"
      "@p st.shared.v2.u32 [%0+16], {%5,%6};\n}\n" ::"r"(a),
      "r"(v[0]), "r"(v[1]), "r"(v[2]), "r"(v[3]), "r"(v[4]), "r"(v[5]), "r"(pred)
      : "memory");
}
__device__ __forceinline__ uint4 lds128(uint32_t a) {
  uint4 v;
  asm volatile("ld.volatile.shared.v4.u32 {%0,%1,%2,%3}, [%4];" : "=r"(v.x), "=r"(v.y), "=r"(v.z), "=r"(v.w) : "r"(a) : "memory");
  return v;
}
__device__ __forceinline__ uint2 lds64(uint32_t a) {
  uint2 v;
  asm volatile("ld.volatile.shared.v2.u32 {%0,%1}, [%2];" : "=r"(v.x), "=r"(v.y) : "r"(a) : "memory");
  return v;
}
__device__ __forceinline__ void mbar_init(uint32_t bar, uint32_t cnt) {
  asm volatile("mbarrier.init.shared::cta.b64 [%0], %1;" ::"r"(bar), "r"(cnt) : "memory");
}
__device__ __forceinline__ void mbar_expect_tx(uint32_t bar, uint32_t bytes) {
  asm volatile("mbarrier.arrive.expect_tx.shared::cta.b64 _, [%0], %1;" ::"r"(bar), "r"(bytes) : "memory");
}
__device__ __forceinline__ void mbar_wait(uint32_t bar, uint32_t parity) {
  uint32_t ok;
  int it = 0;
  do {
    asm volatile(
        "{\n.reg .pred p;\n"
        "mbarrier.try_wait.parity.shared::cta.b64 p, [%1], %2;\n"
        "selp.u32 %0, 1, 0, p;\n}\n"
        : "=r"(ok)
        : "r"(bar), "r"(parity)
        : "memory");
    if (++it > (1 << 22)) __trap();
  } while (!ok);
}
__device__ __forceinline__ uint32_t mbar_try(uint32_t bar, uint32_t parity) {
  uint32_t ok;
  asm volatile(
      "{\n.reg .pred p;\n"
      "mbarrier.test_wait.parity.shared::cta.b64 p, [%1], %2;\n"
      "selp.u32 %0, 1, 0, p;\n}\n"
      : "=r"(ok)
      : "r"(bar), "r"(parity)
      : "memory");
  return ok;
}
__device__ __forceinline__ void mbar_arrive(uint32_t bar) {
  asm volatile("mbarrier.arrive.shared::cta.b64 _, [%0];" ::"r"(bar) : "memory");
}
__device__ __forceinline__ void mbar_arrive_remote(uint32_t rbar) {
  asm volatile("mbarrier.arrive.shared::cluster.b64 _, [%0];" ::"r"(rbar) : "memory");
}
__device__ __forceinline__ uint32_t mapa(uint32_t a, uint32_t rank) {
  uint32_t r;
  asm("mapa.shared::cluster.u32 %0, %1, %2;" : "=r"(r) : "r"(a), "r"(rank));
  return r;
}
__device__ __forceinline__ void st_async128(uint32_t ra, uint32_t x, uint32_t y, uint32_t z, uint32_t w, uint32_t rbar) {
  asm volatile("st.async.weak.shared::cluster.mbarrier::complete_tx::bytes.v4.b32 [%0], {%1,%2,%3,%4}, [%5];" ::"r"(ra),
               "r"(x), "r"(y), "r"(z), "r"(w), "r"(rbar)
               : "memory");
}
__device__ __forceinline__ void tma_row(uint32_t dst, const CUtensorMap* map, int grp, uint32_t bar) {
  asm volatile(
      "cp.async.bulk.tensor.5d.shared::cluster.global.mbarrier::complete_tx::bytes [%0], [%1, {%3, %3, %3, %4, %3}], "
      "[%2];" ::"r"(dst),
      "l"(map), "r"(bar), "r"(0), "r"(grp)
      : "memory");
}
__device__ __forceinline__ void tma_col(uint32_t dst, const CUtensorMap* map, int y, int x, uint32_t bar) {
  asm volatile(
      "cp.async.bulk.tensor.4d.shared::cluster.global.mbarrier::complete_tx::bytes [%0], [%1, {%3, %4, %3, %5}], "
      "[%2];" ::"r"(dst),
      "l"(map), "r"(bar), "r"(0), "r"(y), "r"(x)
      : "memory");
}
__device__ __forceinline__ void bulk_load(uint32_t dst, const void* src, uint32_t bytes, uint32_t bar) {
  asm volatile("cp.async.bulk.shared::cluster.global.mbarrier::complete_tx::bytes [%0], [%1], %2, [%3];" ::"r"(dst),
               "l"(src), "r"(bytes), "r"(bar)
               : "memory");
}
__device__ __forceinline__ void cluster_arrive() { asm volatile("barrier.cluster.arrive.relaxed.aligned;" ::: "memory"); }
__device__ __forceinline__ void cluster_wait() { asm volatile("barrier.cluster.wait.acquire.aligned;" ::: "memory"); }

__device__ __forceinline__ uint32_t wsel(const uint4& v, int i) { return i == 0 ? v.x : i == 1 ? v.y : i == 2 ? v.z : v.w; }
__device__ __forceinline__ int cmap(int j, int q, int e) { return j < 4 ? 8 * q + 2 * j + e : 32 + 4 * q + 2 * (j - 4) + e; }

struct DRow {
  uint32_t o0[6], o1[6];
};
struct PRow {
  uint4 a;
  uint2 b;
};
__device__ __forceinline__ uint32_t pw(const PRow& p, int j) {
  return j == 0 ? p.a.x : j == 1 ? p.a.y : j == 2 ? p.a.z : j == 3 ? p.a.w : j == 4 ? p.b.x : p.b.y;
}
template <bool ADD>
__device__ __forceinline__ uint32_t top(uint32_t a, uint32_t b) {
  return ADD ? hadd2(a, b) : hsub2(a, b);
}
template <bool ADD>
__device__ __forceinline__ void edges(uint32_t (&te)[6], uint32_t ra, uint32_t rb) {
  const uint4 a = lds128(ra), b = lds128(rb);
  const uint2 c = lds64(ra + 16), d = lds64(rb + 16);
  te[0] = top<ADD>(a.x, b.x);
  te[1] = top<ADD>(a.y, b.y);
  te[2] = top<ADD>(a.z, b.z);
  te[3] = top<ADD>(a.w, b.w);
  te[4] = top<ADD>(c.x, d.x);
  te[5] = top<ADD>(c.y, d.y);
}
template <bool ADD>
__device__ __forceinline__ void frags(uint32_t (&f)[12], const DRow& a, const DRow& b, const uint32_t (&te)[6], int ks,
                                      bool e0, bool e7) {
#pragma unroll
  for (int i = 0; i < 2; i++) {
    const int j = 2 * ks + i;
    const uint32_t t0 = top<ADD>(a.o0[j], b.o0[j]), t1 = top<ADD>(a.o1[j], b.o1[j]);
    const uint32_t nA = __shfl_up_sync(0xffffffffu, t1, 4);
    const uint32_t nB = __shfl_down_sync(0xffffffffu, t0, 4);
    f[0 + 2 * i] = e0 ? te[j] : nA;
    f[1 + 2 * i] = t0;
    f[4 + 2 * i] = t0;
    f[5 + 2 * i] = t1;
    f[8 + 2 * i] = t1;
    f[9 + 2 * i] = e7 ? te[j] : nB;
  }
}
template <int MODE>
__device__ __forceinline__ void fr1(uint32_t (&f)[12], const DRow& a, const DRow& b, int ks) {
#pragma unroll
  for (int i = 0; i < 2; i++) {
    const int j = 2 * ks + i;
    const uint32_t t0 = MODE == 0 ? a.o0[j] : top<MODE == 1>(a.o0[j], b.o0[j]);
    const uint32_t t1 = MODE == 0 ? a.o1[j] : top<MODE == 1>(a.o1[j], b.o1[j]);
    f[0 + 2 * i] = __shfl_up_sync(0xffffffffu, t1, 4);
    f[9 + 2 * i] = __shfl_down_sync(0xffffffffu, t0, 4);
    f[1 + 2 * i] = t0;
    f[4 + 2 * i] = t0;
    f[5 + 2 * i] = t1;
    f[8 + 2 * i] = t1;
  }
}
__device__ __forceinline__ void fr2(uint32_t (&f)[12], const uint32_t (&te)[6], int ks, bool e0, bool e7) {
#pragma unroll
  for (int i = 0; i < 2; i++) {
    f[0 + 2 * i] = e0 ? te[2 * ks + i] : f[0 + 2 * i];
    f[9 + 2 * i] = e7 ? te[2 * ks + i] : f[9 + 2 * i];
    asm volatile("" : "+r"(f[0 + 2 * i]), "+r"(f[9 + 2 * i]));
  }
}
struct ERaw {
  uint4 a, b;
  uint2 c, d;
};
__device__ __forceinline__ void ed1(ERaw& r, uint32_t ra, uint32_t rb) {
  r.a = lds128(ra);
  r.b = lds128(rb);
  r.c = lds64(ra + 16);
  r.d = lds64(rb + 16);
}
template <bool ADD>
__device__ __forceinline__ void ed2(uint32_t (&te)[6], const ERaw& r) {
  te[0] = top<ADD>(r.a.x, r.b.x);
  te[1] = top<ADD>(r.a.y, r.b.y);
  te[2] = top<ADD>(r.a.z, r.b.z);
  te[3] = top<ADD>(r.a.w, r.b.w);
  te[4] = top<ADD>(r.c.x, r.d.x);
  te[5] = top<ADD>(r.c.y, r.d.y);
}
template <int INIT>
__device__ __forceinline__ void conv_group(float (&acc)[48], const uint32_t (&f)[12], uint32_t dB, int pos, int ks) {
  wg_fence();
  wgmma_rs_n96<INIT>(acc, f[0], f[1], f[2], f[3], dB + (uint32_t)(((3 * pos + 0) * UT + 2 * ks * 1536) >> 4));
  wgmma_rs_n96<0>(acc, f[4], f[5], f[6], f[7], dB + (uint32_t)(((3 * pos + 1) * UT + 2 * ks * 1536) >> 4));
  wgmma_rs_n96<0>(acc, f[8], f[9], f[10], f[11], dB + (uint32_t)(((3 * pos + 2) * UT + 2 * ks * 1536) >> 4));
  wg_commit();
}
template <int CH, int INIT>
__device__ __forceinline__ void lateral(float (&acc)[24], uint32_t dA, uint32_t dwl) {
  wg_fence();
#pragma unroll
  for (int k = 0; k < 6; k++) {
    const uint32_t a = dA + (uint32_t)(((k >> 1) * CH + (k & 1) * 32) >> 4);
    const uint32_t b = dwl + (uint32_t)(k * 1536 >> 4);
    if (k == 0)
      wgmma_ss_n48<INIT>(acc, a, b);
    else
      wgmma_ss_n48<0>(acc, a, b);
  }
  wg_commit();
}

#define AI __attribute__((always_inline))
template <int V>
struct IC {
  static constexpr int value = V;
};

template <int RANK>
__device__ __forceinline__ void fpn_body(const CUtensorMap& map_row, const CUtensorMap& map_col,
                                         const __nv_bfloat16* __restrict__ p_coarse,
                                         const __nv_bfloat16* __restrict__ w_lat,
                                         const __nv_bfloat16* __restrict__ w_out, __nv_bfloat16* __restrict__ out) {
  extern __shared__ __align__(1024) unsigned char smem[];
  const uint32_t sb = (uint32_t)__cvta_generic_to_shared(smem);
  if ((sb & 0xFFFFFFu) != SB0) __trap();
  const int tid = threadIdx.x;
  const int wg = __shfl_sync(0xffffffffu, tid >> 7, 0);
  const int t128 = tid & 127;
  const int w = __shfl_sync(0xffffffffu, (tid >> 5) & 3, 0);
  const int lane = tid & 31;
  const int g = lane >> 2, q = lane & 3;
  constexpr uint32_t rank = RANK;
  const int cl = blockIdx.x >> 1;
  const int y0 = (cl >> 2) * 32;
  const int x0 = ((cl & 3) * 2 + wg) * 64;

  uint4 wv[8];
  const bool wl_thr = tid >= 32 && tid < 104;
  const int wl_kc = (tid - 32) / 6, wl_u = (tid - 32) % 6;
  if (wl_thr) {
#pragma unroll
    for (int kk = 0; kk < 8; kk++)
      wv[kk] = ldg128((const unsigned char*)w_lat + ((size_t)(8 * wl_kc + kk) * 96 + 48 * rank + 8 * wl_u) * 2);
  }
  uint32_t ticket = 0;
  if (tid >= 224) {
    const int idx = blockIdx.x * 14 + lane;
    if (lane < 14 && idx < 1728) {
      const int wd = idx & 3, t = idx >> 2, rk = t / 216, rem = t % 216, dj = rem / 72, kc = (rem % 72) / 12, u = rem % 12;
      const unsigned char* src = (const unsigned char*)w_out + ((size_t)(dj * 96 + 48 * rk) * 96 + 8 * u) * 2 + 4 * wd;
      uint32_t v[3][8];
#pragma unroll
      for (int kk = 0; kk < 8; kk++) {
        const int ci = cmap(kc, kk >> 1, kk & 1);
#pragma unroll
        for (int di = 0; di < 3; di++) v[di][kk] = __ldg((const uint32_t*)(src + (size_t)di * 3 * 96 * 192 + ci * 192));
      }
      uint32_t u0[2][4], u1[2][4], u2[2][4], u3[2][4];
#pragma unroll
      for (int kp = 0; kp < 4; kp++) {
        const uint32_t a0 = v[0][2 * kp], a1 = v[0][2 * kp + 1];
        const uint32_t b0 = v[1][2 * kp], b1 = v[1][2 * kp + 1];
        const uint32_t c0 = v[2][2 * kp], c1 = v[2][2 * kp + 1];
        u0[0][kp] = __byte_perm(a0, a1, 0x5410);
        u0[1][kp] = __byte_perm(a0, a1, 0x7632);
        u3[0][kp] = __byte_perm(c0, c1, 0x5410);
        u3[1][kp] = __byte_perm(c0, c1, 0x7632);
        const float s0l = bf_lo(a0) + bf_lo(c0), s1l = bf_lo(a1) + bf_lo(c1);
        const float s0h = bf_hi(a0) + bf_hi(c0), s1h = bf_hi(a1) + bf_hi(c1);
        u1[0][kp] = pack_bf16((s0l + bf_lo(b0)) * 0.5f, (s1l + bf_lo(b1)) * 0.5f);
        u1[1][kp] = pack_bf16((s0h + bf_hi(b0)) * 0.5f, (s1h + bf_hi(b1)) * 0.5f);
        u2[0][kp] = pack_bf16((s0l - bf_lo(b0)) * 0.5f, (s1l - bf_lo(b1)) * 0.5f);
        u2[1][kp] = pack_bf16((s0h - bf_hi(b0)) * 0.5f, (s1h - bf_hi(b1)) * 0.5f);
      }
      unsigned char* dst = g_u + rk * 12 * UT + dj * UT + kc * 1536 + (32 * (u >> 2) + 2 * (u & 3) + 8 * wd) * 16;
#pragma unroll
      for (int e = 0; e < 2; e++) {
        *(uint4*)(dst + e * 16) = make_uint4(u0[e][0], u0[e][1], u0[e][2], u0[e][3]);
        *(uint4*)(dst + e * 16 + 3 * UT) = make_uint4(u1[e][0], u1[e][1], u1[e][2], u1[e][3]);
        *(uint4*)(dst + e * 16 + 6 * UT) = make_uint4(u2[e][0], u2[e][1], u2[e][2], u2[e][3]);
        *(uint4*)(dst + e * 16 + 9 * UT) = make_uint4(u3[e][0], u3[e][1], u3[e][2], u3[e][3]);
      }
      asm volatile("fence.proxy.async.global;" ::: "memory");
    }
    __syncwarp();
    if (lane == 0) asm volatile("atom.release.gpu.global.add.u32 %0, [%1], 1;" : "=r"(ticket) : "l"(&g_cnt) : "memory");
  }
  if (tid == 0) {
#pragma unroll
    for (int i = 0; i < 2; i++) {
      const uint32_t b = sb + OFF_BAR + i * 64;
      mbar_init(b + 0, 1);
      mbar_init(b + 8, 1);
      mbar_init(b + 16, 1);
      mbar_init(b + 24, 1);
      mbar_init(b + 32, 4);
      mbar_init(b + 40, 4);
      mbar_init(b + 48, 1);
      mbar_init(b + 56, 4);
      mbar_init(sb + OFF_BAR + 128 + i * 16, 1);
      mbar_init(sb + OFF_BAR + 136 + i * 16, 1);
    }
    asm volatile("fence.mbarrier_init.release.cluster;" ::: "memory");
    fence_async_smem();
#pragma unroll
    for (int i = 0; i < 2; i++) {
      const uint32_t b = sb + OFF_BAR + i * 64;
      const int xw = ((cl & 3) * 2 + i) * 64;
      mbar_expect_tx(b + 48, 2 * HTILE);
      tma_col(sb + OFF_X + i * X_BYTES, &map_col, y0 - 1, xw - 1, b + 48);
      tma_col(sb + OFF_X + i * X_BYTES + HTILE, &map_col, y0 - 1, xw + 64, b + 48);
      mbar_expect_tx(b + 0, 2 * CSLOT);
      tma_row(sb + OFF_C + i * 2 * CSLOT, &map_row, (y0 - 1) * 32 + (xw >> 4), b + 0);
      tma_row(sb + OFF_H + i * HE_BYTES, &map_row, (y0 + 1) * 32 + (xw >> 4), b + 0);
      mbar_expect_tx(b + 8, CSLOT);
      tma_row(sb + OFF_C + i * 2 * CSLOT + CSLOT, &map_row, y0 * 32 + (xw >> 4), b + 8);
      mbar_expect_tx(b + 16, XROW);
      mbar_expect_tx(b + 24, XROW);
    }
  }
  cluster_arrive();

  if (wl_thr) {
    {
      const int kc = wl_kc, u = wl_u;
      const uint4(&v)[8] = wv;
#pragma unroll
      for (int wd = 0; wd < 4; wd++) {
        const int n = u < 4 ? 8 * wd + 2 * u : 8 * (4 + (wd & 1)) + 2 * (2 * (u - 4) + (wd >> 1));
        const uint32_t a = sb + OFF_WL + kc * 768 + n * 16;
        uint32_t lo[4], hi[4];
#pragma unroll
        for (int kp = 0; kp < 4; kp++) {
          lo[kp] = __byte_perm(wsel(v[2 * kp], wd), wsel(v[2 * kp + 1], wd), 0x5410);
          hi[kp] = __byte_perm(wsel(v[2 * kp], wd), wsel(v[2 * kp + 1], wd), 0x7632);
        }
        sts128(a, lo[0], lo[1], lo[2], lo[3]);
        sts128(a + 16, hi[0], hi[1], hi[2], hi[3]);
      }
    }
    fence_async_smem();
  }
  const unsigned char* pc = (const unsigned char*)p_coarse + 96 * rank;

  PRow hp[2][2], pA, pp;
  bool hv[2][2];
#pragma unroll
  for (int sd = 0; sd < 2; sd++)
#pragma unroll
    for (int h = 0; h < 2; h++) {
      const int hr = 16 * w + 8 * h + g, yy = y0 - 1 + hr, xx = sd ? x0 + 64 : x0 - 1;
      hv[sd][h] = hr < 34 && yy >= 0 && yy < IMG && xx >= 0 && xx < IMG;
      const unsigned char* a = pc + (hv[sd][h] ? ((size_t)(yy >> 1) * 256 + (xx >> 1)) * 192 : 0);
      hp[sd][h].a = ldg128(a + 16 * q);
      hp[sd][h].b = ldg64(a + 64 + 8 * q);
    }
  uint32_t poff = ((y0 >> 1) * 256 + (x0 >> 1) + 8 * w + g) * 192 + 16 * q;
  {
    const unsigned char* a = pc + poff - (y0 > 0 ? 49152 : 0);
    pA.a = ldg128(a);
    pA.b = ldg64(a + 64 - 8 * q);
    pp.a = ldg128(pc + poff);
    pp.b = ldg64(pc + poff + 64 - 8 * q);
    poff += 49152;
  }

  __syncthreads();
  cluster_wait();

  const uint32_t bb = sb + OFF_BAR + wg * 64;
  constexpr uint32_t dwl = make_desc(SB0 + OFF_WL, 768);
  constexpr uint32_t dB = make_desc(SB0 + OFF_U, 1536);
  const uint32_t cs = sb + OFF_C + wg * 2 * CSLOT;
  const uint32_t dC = make_desc(SB0 + OFF_C, 16) + wg * (2 * CSLOT >> 4);
  const uint32_t xbase = sb + OFF_X + wg * X_BYTES;
  const uint32_t dH = make_desc(SB0 + OFF_X, 16) + wg * (X_BYTES >> 4);
  const uint32_t hb = sb + OFF_H + wg * HE_BYTES;
  const uint32_t eb = hb + H_BYTES;
  const uint32_t ub = sb + OFF_BAR + 128;
  const uint32_t xa = xbase + t128 * 16;
  const uint32_t peer = rank ^ 1;
  const uint32_t rdelta = __shfl_sync(0xffffffffu, mapa(bb, peer) - bb, 0);
#define r_xa (xa + rdelta)
#define r_bb (bb + rdelta)
  const int grp0 = (y0 - 1) * 32 + (x0 >> 4);
  const bool last_block = (y0 + 32 == IMG);

  const bool e0 = g == 0, e7 = g == 7;
  const bool halo_lane = (w == 0 && g < 4) || (w == 3 && g >= 4);
  const uint32_t ewr = eb + (2 * w + (e7 ? 1 : 0)) * 512 + 32 * q;
  const uint32_t erd =
      (halo_lane ? (g < 4 ? hb : hb + HSIDE) : (g < 4 ? eb + (2 * w - 1) * 512 : eb + (2 * w + 2) * 512)) + 32 * q;
  const uint32_t emask = halo_lane ? 0xFFFFu : 511u;
  auto er = [&](int k) AI { return erd + (((uint32_t)k << 8) & emask); };

  float ax[48], ay[48], lat[24];
  DRow d1, d2, t0, t3;
  uint32_t f0[12], f1[12], f2[12], te[6], kp[12];
#pragma unroll
  for (int i = 0; i < 12; i++) kp[i] = 0;

  auto d_pack = [&](auto MODE, int i, DRow& d, DRow& t, const float(&acc)[24], const PRow& p, bool zero) AI {
    constexpr int mode = decltype(MODE)::value;
#pragma unroll
    for (int j = 0; j < 6; j++) {
      uint32_t n0 = hadd2(pack_bf16(acc[4 * j], acc[4 * j + 1]), pw(p, j));
      uint32_t n1 = hadd2(pack_bf16(acc[4 * j + 2], acc[4 * j + 3]), pw(p, j));
      if (zero) n0 = n1 = 0;
      if (mode == 1) {
        t.o0[j] = hsub2(n0, d.o0[j]);
        t.o1[j] = hsub2(n1, d.o1[j]);
      }
      if (mode == 2) {
        t.o0[j] = hsub2(d.o0[j], n0);
        t.o1[j] = hsub2(d.o1[j], n1);
      }
      d.o0[j] = n0;
      d.o1[j] = n1;
    }
    uint32_t ev[6];
#pragma unroll
    for (int j = 0; j < 6; j++) ev[j] = e0 ? d.o0[j] : d.o1[j];
    sts24_pred(ewr + (i & 3) * 128, ev, e0 || e7);
    if (mode != 0) {
      __syncwarp();
      if (lane == 0) mbar_arrive(bb + 56);
    }
  };
  auto refill = [&](int i) AI {
    if (t128 == 0 && i + 2 <= 33) {
      mbar_expect_tx(bb + (i & 1) * 8, CSLOT);
      tma_row(cs + (i & 1) * CSLOT, &map_row, grp0 + (i + 2) * 32, bb + (i & 1) * 8);
    }
  };
  auto send = [&](const float(&acc)[48], int b) AI {
    constexpr int rk = RANK;
#pragma unroll
    for (int J = 0; J < 3; J++) {
      uint32_t sd[4];
#pragma unroll
      for (int i = 0; i < 4; i++) {
        const int j = 4 * J + i;
        sd[i] = pack_bf16(acc[4 * j + 2 - 2 * rk], acc[4 * j + 3 - 2 * rk]);
        kp[j] = pack_bf16(acc[4 * j + 2 * rk], acc[4 * j + 2 * rk + 1]);
      }
      st_async128(r_xa + b * XROW + J * 2048, sd[0], sd[1], sd[2], sd[3], r_bb + 16 + 8 * b);
    }
  };
  uint32_t ooff = ((y0 * IMG) + x0 + 16 * w + 2 * g + rank) * 192 + 16 * q;
  uint4 xr[3];
  auto fin1 = [&](int b) AI {
#pragma unroll
    for (int J = 0; J < 3; J++) xr[J] = lds128(xa + b * XROW + J * 2048);
  };
  auto fin2 = [&](int b, uint32_t parity, uint32_t ok, bool more) AI {
    if (!ok) {
      mbar_wait(bb + 16 + 8 * b, parity);
      fin1(b);
    }
    if (more && t128 == 0) mbar_expect_tx(bb + 16 + 8 * b, XROW);
#pragma unroll
    for (int J = 0; J < 3; J++) {
      uint4 o;
      o.x = hadd2(kp[4 * J + 0], xr[J].x);
      o.y = hadd2(kp[4 * J + 1], xr[J].y);
      o.z = hadd2(kp[4 * J + 2], xr[J].z);
      o.w = hadd2(kp[4 * J + 3], xr[J].w);
      __stcs((uint4*)((unsigned char*)out + (ooff + 64 * J)), o);
    }
    ooff += 98304;
    __syncwarp();
    if (more && lane == 0) mbar_arrive_remote(r_bb + 32 + 8 * b);
  };

  {
    float lat2[24], lr0[24], lr1[24], lr2[24];
    mbar_wait(bb + 48, 0);
    lateral<2560, 1>(lat, dH, dwl);
    lateral<2560, 1>(lat2, dH + (HTILE >> 4), dwl);
    mbar_wait(bb + 8, 0);
    lateral<4096, 1>(lr1, dC + (CSLOT >> 4), dwl);
    mbar_wait(bb + 0, 0);
    lateral<4096, 1>(lr0, dC, dwl);
    lateral<4096, 1>(lr2, make_desc(SB0 + OFF_H, 16) + wg * (HE_BYTES >> 4), dwl);
    if (tid == 224) {
      const uint32_t target = (ticket | 127u) + 1u;
      uint32_t c, n = 0;
      do {
        asm volatile("ld.acquire.gpu.global.u32 %0, [%1];" : "=r"(c) : "l"(&g_cnt) : "memory");
        if (++n > (1u << 22)) __trap();
      } while ((int)(c - target) < 0);
      asm volatile("fence.proxy.async.global;" ::: "memory");
#pragma unroll
      for (int i = 0; i < 4; i++) {
        const int pos = i == 0 ? 1 : i == 1 ? 2 : i == 2 ? 0 : 3;
        mbar_expect_tx(ub + 8 * pos, 3 * UT);
        bulk_load(sb + OFF_U + pos * 3 * UT, g_u + (rank * 12 + pos * 3) * UT, 3 * UT, ub + 8 * pos);
      }
    }
    __syncwarp();
    wg_wait<0>();
    fence_regs(lat);
    fence_regs(lat2);
    fence_regs(lr0);
    fence_regs(lr1);
    fence_regs(lr2);
    asm volatile("bar.sync %0, 128;" ::"r"(wg + 1) : "memory");
    refill(1);
    refill(2);
    __syncwarp();
    if (lane == 0) {
      mbar_arrive_remote(r_bb + 32);
      mbar_arrive_remote(r_bb + 40);
    }
#pragma unroll
    for (int h = 0; h < 2; h++) {
      const int hr = 16 * w + 8 * h + g;
      uint32_t v0[6], v1[6];
#pragma unroll
      for (int j = 0; j < 6; j++) {
        v0[j] = hv[0][h] ? hadd2(pack_bf16(lat[4 * j + 2 * h], lat[4 * j + 2 * h + 1]), pw(hp[0][h], j)) : 0u;
        v1[j] = hv[1][h] ? hadd2(pack_bf16(lat2[4 * j + 2 * h], lat2[4 * j + 2 * h + 1]), pw(hp[1][h], j)) : 0u;
      }
      sts24_pred(hb + hr * 128 + 32 * q, v0, hr < 34);
      sts24_pred(hb + HSIDE + hr * 128 + 32 * q, v1, hr < 34);
    }
    d_pack(IC<0>{}, 0, d2, t0, lr0, pA, y0 == 0);
    d_pack(IC<0>{}, 1, d1, t3, lr1, pp, false);
    d_pack(IC<2>{}, 2, d2, t0, lr2, pp, false);
    mbar_wait(bb + 56, 0);
    pp.a = ldg128(pc + poff);
    pp.b = ldg64(pc + poff + 64 - 8 * q);
    edges<true>(te, er(0) + 128, er(1));
    frags<true>(f0, d1, d2, te, 0, e0, e7);
    mbar_wait(ub + 8, 0);
    conv_group<1>(ax, f0, dB, 1, 0);
    frags<true>(f1, d1, d2, te, 1, e0, e7);
  }

  ERaw er4;
  uint32_t ok1, ok2;
#define CUT sched_cut<__LINE__>(cl)
  auto stepA = [&](auto FIRST, int s) AI {
    constexpr bool notfirst = !decltype(FIRST)::value;
    const uint32_t par = s & 1;
    wg_wait<1>();
    if (notfirst) fence_regs(ay);
    CUT;
    fr1<1>(f2, d1, d2, 2);
    if (notfirst && ok1) fin1(0);
    CUT;
    conv_group<0>(ax, f1, dB, 1, 1);
    CUT;
    if (notfirst) fin2(0, par ^ 1, ok1, true);
    fr2(f2, te, 2, e0, e7);
    wg_wait<1>();
    CUT;
    ed1(er4, er(s + 1), er(s) + 128);
    fr1<2>(f0, d2, d1, 0);
    if (notfirst) ok2 = mbar_try(bb + 40, par ^ 1);
    CUT;
    conv_group<0>(ax, f2, dB, 1, 2);
    CUT;
    if (notfirst) {
      if (!ok2) mbar_wait(bb + 40, par ^ 1);
      send(ay, 1);
    }
    ed2<false>(te, er4);
    fr2(f0, te, 0, e0, e7);
    wg_wait<1>();
    CUT;
    fr1<2>(f1, d2, d1, 1);
    if (!notfirst) mbar_wait(ub + 16, 0);
    CUT;
    conv_group<notfirst ? 2 : 1>(ay, f0, dB, 2, 0);
    CUT;
    fr2(f1, te, 1, e0, e7);
    wg_wait<1>();
    CUT;
    fr1<2>(f2, d2, d1, 2);
    CUT;
    conv_group<0>(ay, f1, dB, 2, 1);
    CUT;
    fr2(f2, te, 2, e0, e7);
    wg_wait<1>();
    CUT;
    ed1(er4, er(s), er(s + 1));
    fr1<0>(f0, t0, t0, 0);
    ok1 = mbar_try(bb + 8, par ^ 1);
    CUT;
    conv_group<0>(ay, f2, dB, 2, 2);
    CUT;
    ed2<false>(te, er4);
    fr2(f0, te, 0, e0, e7);
    if (!ok1) mbar_wait(bb + 8, par ^ 1);
    wg_wait<1>();
    CUT;
    fr1<0>(f1, t0, t0, 1);
    CUT;
    lateral<4096, 2>(lat, dC + (CSLOT >> 4), dwl);
    CUT;
    fr2(f1, te, 1, e0, e7);
    if (!notfirst) {
      mbar_wait(ub + 0, 0);
      mbar_wait(ub + 24, 0);
    }
    CUT;
    wg_wait<1>();
    fence_regs(ax);
    fence_regs(ay);
  };
  auto stepB = [&](auto LAST, int s) AI {
    constexpr bool notlast = !decltype(LAST)::value;
    const uint32_t par = s & 1;
    fr1<0>(f2, t0, t0, 2);
    if (notlast) ok2 = mbar_try(bb + 0, par ^ 1);
    ok1 = mbar_try(bb + 24, par ^ 1);
    CUT;
#pragma unroll
    for (int i = 0; i < 48; i++) {
      asm volatile("add.f32 %0, %0, %1;\n\tfma.rn.f32 %1, %1, 0fC0000000, %0;" : "+f"(ax[i]), "+f"(ay[i]));
    }
    fence_regs(ax);
    fence_regs(ay);
    conv_group<0>(ax, f0, dB, 0, 0);
    wg_wait<1>();
    fence_regs(lat);
    CUT;
    d_pack(IC<1>{}, 2 * s + 3, d1, t3, lat, pp, last_block && !notlast);
    fr2(f2, te, 2, e0, e7);
    if (notlast && !ok2) mbar_wait(bb + 0, par ^ 1);
    if (ok1) fin1(1);
    CUT;
    if (notlast) lateral<4096, 2>(lat, dC, dwl);
    CUT;
    if (s > 0) fin2(1, par ^ 1, ok1, true);
    wg_wait<notlast ? 1 : 0>();
    CUT;
    ok1 = mbar_try(bb + 56, 1);
    fr1<0>(f0, t3, t3, 0);
    CUT;
    conv_group<0>(ax, f1, dB, 0, 1);
    CUT;
    if (!ok1) mbar_wait(bb + 56, 1);
    refill(2 * s + 3);
    if (notlast) {
      wg_wait<1>();
      fence_regs(lat);
      CUT;
    }
    ed1(er4, er(s + 1) + 128, er(s) + 128);
    if (notlast) {
      d_pack(IC<2>{}, 2 * s + 4, d2, t0, lat, pp, false);
      if ((y0 >> 1) + s + 2 < 256) poff += 49152;
      pp.a = ldg128(pc + poff);
      pp.b = ldg64(pc + poff + 64 - 8 * q);
    }
    CUT;
    conv_group<0>(ax, f2, dB, 0, 2);
    CUT;
    ed2<false>(te, er4);
    fr2(f0, te, 0, e0, e7);
    wg_wait<1>();
    keep(f1);
    CUT;
    fr1<0>(f1, t3, t3, 1);
    if (notlast) ok1 = mbar_try(bb + 56, 0);
    CUT;
    conv_group<0>(ay, f0, dB, 3, 0);
    CUT;
    fr2(f1, te, 1, e0, e7);
    if (notlast) {
      if (!ok1) mbar_wait(bb + 56, 0);
      refill(2 * s + 4);
    }
    wg_wait<1>();
    fence_regs(ax);
    keep(f2);
    CUT;
    fr1<0>(f2, t3, t3, 2);
    ok2 = mbar_try(bb + 32, par);
    CUT;
    conv_group<0>(ay, f1, dB, 3, 1);
    CUT;
    if (!ok2) mbar_wait(bb + 32, par);
    send(ax, 0);
    fr2(f2, te, 2, e0, e7);
    if (notlast) {
      wg_wait<1>();
      CUT;
      ed1(er4, er(s + 1) + 128, er(s + 2));
      fr1<1>(f0, d1, d2, 0);
    }
    CUT;
    conv_group<0>(ay, f2, dB, 3, 2);
    if (notlast) {
      CUT;
      ed2<true>(te, er4);
      fr2(f0, te, 0, e0, e7);
      wg_wait<1>();
      CUT;
      fr1<1>(f1, d1, d2, 1);
      ok1 = mbar_try(bb + 16, par);
      CUT;
      conv_group<2>(ax, f0, dB, 1, 0);
      CUT;
      fr2(f1, te, 1, e0, e7);
    }
  };

  stepA(IC<1>{}, 0);
#pragma unroll 1
  for (int s = 0; s < NSTEP - 1; s++) {
    stepB(IC<0>{}, s);
    stepA(IC<0>{}, s + 1);
  }
  stepB(IC<1>{}, NSTEP - 1);
  fin2(0, 1, 0, false);
  wg_wait<0>();
  fence_regs(ay);
  mbar_wait(bb + 40, 1);
  send(ay, 1);
  fin2(1, 1, 0, false);
}

__global__ void __cluster_dims__(2, 1, 1) __launch_bounds__(256, 1)
    fpn_kernel(const __grid_constant__ CUtensorMap map_row, const __grid_constant__ CUtensorMap map_col,
               const __nv_bfloat16* __restrict__ p_coarse, const __nv_bfloat16* __restrict__ w_lat,
               const __nv_bfloat16* __restrict__ w_out, __nv_bfloat16* __restrict__ out) {
  uint32_t rank;
  asm("mov.u32 %0, %%cluster_ctarank;" : "=r"(rank));
  if (rank)
    fpn_body<1>(map_row, map_col, p_coarse, w_lat, w_out, out);
  else
    fpn_body<0>(map_row, map_col, p_coarse, w_lat, w_out, out);
}

typedef CUresult (*EncodeFn)(CUtensorMap*, CUtensorMapDataType, cuuint32_t, void*, const cuuint64_t*, const cuuint64_t*,
                             const cuuint32_t*, const cuuint32_t*, CUtensorMapInterleave, CUtensorMapSwizzle,
                             CUtensorMapL2promotion, CUtensorMapFloatOOBfill);

}

extern "C" void kernel_launch(void* const* d_in, const int* in_sizes, int n_in, void* d_out, int out_size) {
  (void)in_sizes;
  (void)n_in;
  (void)out_size;
  static EncodeFn encode = nullptr;
  if (!encode) {
    cudaFuncSetAttribute(fpn_kernel, cudaFuncAttributeMaxDynamicSharedMemorySize, SMEM_BYTES);
    void* fn = nullptr;
    cudaDriverEntryPointQueryResult st;
    cudaGetDriverEntryPoint("cuTensorMapEncodeTiled", &fn, cudaEnableDefault, &st);
    encode = (EncodeFn)fn;
  }
  CUtensorMap map_row, map_col;
  {
    const cuuint64_t dim[5] = {32, 8, 2, 16384, 3};
    const cuuint64_t str[4] = {384, 192, 3072, 64};
    const cuuint32_t box[5] = {32, 8, 2, 4, 3};
    const cuuint32_t es[5] = {1, 1, 1, 1, 1};
    encode(&map_row, CU_TENSOR_MAP_DATA_TYPE_BFLOAT16, 5, d_in[0], dim, str, box, es, CU_TENSOR_MAP_INTERLEAVE_NONE,
           CU_TENSOR_MAP_SWIZZLE_64B, CU_TENSOR_MAP_L2_PROMOTION_L2_256B, CU_TENSOR_MAP_FLOAT_OOB_FILL_NONE);
  }
  {
    const cuuint64_t dim[4] = {32, 512, 3, 512};
    const cuuint64_t str[3] = {98304, 64, 192};
    const cuuint32_t box[4] = {32, 40, 3, 1};
    const cuuint32_t es[4] = {1, 1, 1, 1};
    encode(&map_col, CU_TENSOR_MAP_DATA_TYPE_BFLOAT16, 4, d_in[0], dim, str, box, es, CU_TENSOR_MAP_INTERLEAVE_NONE,
           CU_TENSOR_MAP_SWIZZLE_64B, CU_TENSOR_MAP_L2_PROMOTION_L2_128B, CU_TENSOR_MAP_FLOAT_OOB_FILL_NONE);
  }
  fpn_kernel<<<128, 256, SMEM_BYTES, cudaStreamPerThread>>>(map_row, map_col, (const __nv_bfloat16*)d_in[1],
                                                            (const __nv_bfloat16*)d_in[2], (const __nv_bfloat16*)d_in[3],
                                                            (__nv_bfloat16*)d_out);
}
```

```cpp
#include <cuda_runtime.h>
#include <cuda.h>
#include <cuda_bf16.h>
#include <stdint.h>

namespace {

constexpr int IMG = 512;
constexpr int CSLOT = 12288;
constexpr int UT = 9216;
constexpr int OFF_C = 0;
constexpr int OFF_U = 4 * CSLOT;
constexpr int OFF_WL = OFF_U + 12 * UT;
constexpr int OFF_X = OFF_WL + 9216;
constexpr int XROW = 6144;
constexpr int HTILE = 7680;
constexpr int X_BYTES = 2 * HTILE;
constexpr int OFF_H = OFF_X + 2 * X_BYTES;
constexpr int HSIDE = 35 * 128;
constexpr int H_BYTES = 2 * HSIDE;
constexpr int HE_BYTES = 13312;
constexpr int OFF_BAR = OFF_H + 2 * HE_BYTES;
constexpr int SMEM_BYTES = OFF_BAR + 192;
__device__ __align__(1024) unsigned char g_u[2 * 12 * UT];
__device__ unsigned int g_cnt;
constexpr int NSTEP = 16;

#define R4(c, a, o) c(a[o]), c(a[o + 1]), c(a[o + 2]), c(a[o + 3])
#define R8(c, a, o) R4(c, a, o), R4(c, a, o + 4)
#define R24(c, a, o) R8(c, a, o), R8(c, a, o + 8), R8(c, a, o + 16)
#define RL24 \
  "%0, %1, %2, %3, %4, %5, %6, %7, %8, %9, %10, %11, %12, %13, %14, %15, %16, %17, %18, %19, %20, %21, %22, %23"
#define RL48                                                                                                       \
  RL24 ", %24, %25, %26, %27, %28, %29, %30, %31, %32, %33, %34, %35, %36, %37, %38, %39, %40, %41, %42, %43, %44, " \
       "%45, %46, %47"

constexpr uint32_t HI_W = 128 >> 4;
constexpr uint32_t HI_C = (512 >> 4) | (2u << 30);
template <int INIT>
__device__ __forceinline__ void wgmma_rs_n96(float (&d)[48], uint32_t a0, uint32_t a1, uint32_t a2, uint32_t a3,
                                             uint32_t db) {
  if constexpr (INIT == 1) {
    asm volatile(
        "{\n.reg .pred p;\n.reg .b64 db;\nsetp.ne.b32 p, 0, 0;\nmov.b64 db, {%52, %53};\n"
        "wgmma.mma_async.sync.aligned.m64n96k16.f32.bf16.bf16 {" RL48 "}, {%48, %49, %50, %51}, db, p, 1, 1, 0;\n}\n"
        : R24("=f", d, 0), R24("=f", d, 24)
        : "r"(a0), "r"(a1), "r"(a2), "r"(a3), "r"(db), "n"(HI_W));
  } else {
    asm volatile(
        "{\n.reg .pred p;\n.reg .b64 db;\nsetp.eq.b32 p, %54, 0;\nmov.b64 db, {%52, %53};\n"
        "wgmma.mma_async.sync.aligned.m64n96k16.f32.bf16.bf16 {" RL48 "}, {%48, %49, %50, %51}, db, p, 1, 1, 0;\n}\n"
        : R24("+f", d, 0), R24("+f", d, 24)
        : "r"(a0), "r"(a1), "r"(a2), "r"(a3), "r"(db), "n"(HI_W), "n"(INIT));
  }
}
template <int INIT>
__device__ __forceinline__ void wgmma_ss_n48(float (&d)[24], uint32_t da, uint32_t db) {
  if constexpr (INIT == 1) {
    asm volatile(
        "{\n.reg .pred p;\n.reg .b64 da, db;\nsetp.ne.b32 p, 0, 0;\nmov.b64 da, {%24, %26};\nmov.b64 db, {%25, %27};\n"
        "wgmma.mma_async.sync.aligned.m64n48k16.f32.bf16.bf16 {" RL24 "}, da, db, p, 1, 1, 0, 0;\n}\n"
        : R24("=f", d, 0)
        : "r"(da), "r"(db), "n"(HI_C), "n"(HI_W));
  } else {
    asm volatile(
        "{\n.reg .pred p;\n.reg .b64 da, db;\nsetp.eq.b32 p, %28, 0;\nmov.b64 da, {%24, %26};\nmov.b64 db, {%25, %27};\n"
        "wgmma.mma_async.sync.aligned.m64n48k16.f32.bf16.bf16 {" RL24 "}, da, db, p, 1, 1, 0, 0;\n}\n"
        : R24("+f", d, 0)
        : "r"(da), "r"(db), "n"(HI_C), "n"(HI_W), "n"(INIT));
  }
}
__device__ __forceinline__ void wg_fence() { asm volatile("wgmma.fence.sync.aligned;" ::: "memory"); }
__device__ __forceinline__ void wg_commit() { asm volatile("wgmma.commit_group.sync.aligned;" ::: "memory"); }
template <int K>
__device__ __forceinline__ void sched_cut(uint32_t x) {
  asm volatile("{\n.reg .pred p;\nsetp.eq.u32 p, %0, %1;\n@p trap;\n}\n" ::"r"(x), "n"(100000 + K) : "memory");
}
template <int N>
__device__ __forceinline__ void wg_wait() {
  asm volatile("wgmma.wait_group.sync.aligned %0;" ::"n"(N) : "memory");
}
template <int N>
__device__ __forceinline__ void fence_regs(float (&a)[N]) {
#pragma unroll
  for (int i = 0; i < N; i++) asm volatile("" : "+f"(a[i])::"memory");
}
constexpr uint32_t SB0 = 0x400;
__host__ __device__ constexpr uint32_t make_desc(uint32_t saddr, uint32_t lbo) {
  return ((saddr & 0x3FFFF) >> 4) | ((lbo >> 4) << 16);
}
__device__ __forceinline__ void fence_async_smem() { asm volatile("fence.proxy.async.shared::cta;" ::: "memory"); }
__device__ __forceinline__ void keep(const uint32_t (&f)[12]) {
#pragma unroll
  for (int i = 0; i < 12; i++) asm volatile("" ::"r"(f[i]) : "memory");
}

__device__ __forceinline__ uint32_t pack_bf16(float lo, float hi) {
  uint32_t r;
  asm("cvt.rn.bf16x2.f32 %0, %1, %2;" : "=r"(r) : "f"(hi), "f"(lo));
  return r;
}
__device__ __forceinline__ uint32_t hadd2(uint32_t a, uint32_t b) {
  uint32_t r;
  asm("add.rn.bf16x2 %0, %1, %2;" : "=r"(r) : "r"(a), "r"(b));
  return r;
}
__device__ __forceinline__ uint32_t hsub2(uint32_t a, uint32_t b) {
  uint32_t r;
  asm("sub.rn.bf16x2 %0, %1, %2;" : "=r"(r) : "r"(a), "r"(b));
  return r;
}
__device__ __forceinline__ float bf_lo(uint32_t a) { return __uint_as_float(a << 16); }
__device__ __forceinline__ float bf_hi(uint32_t a) { return __uint_as_float(a & 0xffff0000u); }

__device__ __forceinline__ uint4 ldg128(const void* p) {
  uint4 v;
  asm volatile("ld.global.nc.L1::no_allocate.v4.u32 {%0,%1,%2,%3}, [%4];"
               : "=r"(v.x), "=r"(v.y), "=r"(v.z), "=r"(v.w)
               : "l"(p));
  return v;
}
__device__ __forceinline__ uint2 ldg64(const void* p) {
  uint2 v;
  asm volatile("ld.global.nc.L1::no_allocate.v2.u32 {%0,%1}, [%2];" : "=r"(v.x), "=r"(v.y) : "l"(p));
  return v;
}
__device__ __forceinline__ void sts128(uint32_t a, uint32_t x, uint32_t y, uint32_t z, uint32_t w) {
  asm volatile("st.shared.v4.u32 [%0], {%1,%2,%3,%4};" ::"r"(a), "r"(x), "r"(y), "r"(z), "r"(w) : "memory");
}
__device__ __forceinline__ void sts24_pred(uint32_t a, const uint32_t (&v)[6], uint32_t pred) {
  asm volatile(
      "{\n.reg .pred p;\nsetp.ne.b32 p, %7, 0;\n"
      "@p st.shared.v4.u32 [%0], {%1,%2,%3,%4};\n"
      "@p st.shared.v2.u32 [%0+16], {%5,%6};\n}\n" ::"r"(a),
      "r"(v[0]), "r"(v[1]), "r"(v[2]), "r"(v[3]), "r"(v[4]), "r"(v[5]), "r"(pred)
      : "memory");
}
__device__ __forceinline__ uint4 lds128(uint32_t a) {
  uint4 v;
  asm volatile("ld.volatile.shared.v4.u32 {%0,%1,%2,%3}, [%4];" : "=r"(v.x), "=r"(v.y), "=r"(v.z), "=r"(v.w) : "r"(a) : "memory");
  return v;
}
__device__ __forceinline__ uint2 lds64(uint32_t a) {
  uint2 v;
  asm volatile("ld.volatile.shared.v2.u32 {%0,%1}, [%2];" : "=r"(v.x), "=r"(v.y) : "r"(a) : "memory");
  return v;
}
__device__ __forceinline__ void mbar_init(uint32_t bar, uint32_t cnt) {
  asm volatile("mbarrier.init.shared::cta.b64 [%0], %1;" ::"r"(bar), "r"(cnt) : "memory");
}
__device__ __forceinline__ void mbar_expect_tx(uint32_t bar, uint32_t bytes) {
  asm volatile("mbarrier.arrive.expect_tx.shared::cta.b64 _, [%0], %1;" ::"r"(bar), "r"(bytes) : "memory");
}
__device__ __forceinline__ void mbar_wait(uint32_t bar, uint32_t parity) {
  uint32_t ok;
  int it = 0;
  do {
    asm volatile(
        "{\n.reg .pred p;\n"
        "mbarrier.try_wait.parity.shared::cta.b64 p, [%1], %2;\n"
        "selp.u32 %0, 1, 0, p;\n}\n"
        : "=r"(ok)
        : "r"(bar), "r"(parity)
        : "memory");
    if (++it > (1 << 22)) __trap();
  } while (!ok);
}
__device__ __forceinline__ uint32_t mbar_try(uint32_t bar, uint32_t parity) {
  uint32_t ok;
  asm volatile(
      "{\n.reg .pred p;\n"
      "mbarrier.test_wait.parity.shared::cta.b64 p, [%1], %2;\n"
      "selp.u32 %0, 1, 0, p;\n}\n"
      : "=r"(ok)
      : "r"(bar), "r"(parity)
      : "memory");
  return ok;
}
__device__ __forceinline__ void mbar_arrive(uint32_t bar) {
  asm volatile("mbarrier.arrive.shared::cta.b64 _, [%0];" ::"r"(bar) : "memory");
}
__device__ __forceinline__ void mbar_arrive_remote(uint32_t rbar) {
  asm volatile("mbarrier.arrive.shared::cluster.b64 _, [%0];" ::"r"(rbar) : "memory");
}
__device__ __forceinline__ uint32_t mapa(uint32_t a, uint32_t rank) {
  uint32_t r;
  asm("mapa.shared::cluster.u32 %0, %1, %2;" : "=r"(r) : "r"(a), "r"(rank));
  return r;
}
__device__ __forceinline__ void st_async128(uint32_t ra, uint32_t x, uint32_t y, uint32_t z, uint32_t w, uint32_t rbar) {
  asm volatile("st.async.weak.shared::cluster.mbarrier::complete_tx::bytes.v4.b32 [%0], {%1,%2,%3,%4}, [%5];" ::"r"(ra),
               "r"(x), "r"(y), "r"(z), "r"(w), "r"(rbar)
               : "memory");
}
__device__ __forceinline__ void tma_row(uint32_t dst, const CUtensorMap* map, int grp, uint32_t bar) {
  asm volatile(
      "cp.async.bulk.tensor.5d.shared::cluster.global.mbarrier::complete_tx::bytes [%0], [%1, {%3, %3, %3, %4, %3}], "
      "[%2];" ::"r"(dst),
      "l"(map), "r"(bar), "r"(0), "r"(grp)
      : "memory");
}
__device__ __forceinline__ void tma_col(uint32_t dst, const CUtensorMap* map, int y, int x, uint32_t bar) {
  asm volatile(
      "cp.async.bulk.tensor.4d.shared::cluster.global.mbarrier::complete_tx::bytes [%0], [%1, {%3, %4, %3, %5}], "
      "[%2];" ::"r"(dst),
      "l"(map), "r"(bar), "r"(0), "r"(y), "r"(x)
      : "memory");
}
__device__ __forceinline__ void bulk_load(uint32_t dst, const void* src, uint32_t bytes, uint32_t bar) {
  asm volatile("cp.async.bulk.shared::cluster.global.mbarrier::complete_tx::bytes [%0], [%1], %2, [%3];" ::"r"(dst),
               "l"(src), "r"(bytes), "r"(bar)
               : "memory");
}
__device__ __forceinline__ void cluster_arrive() { asm volatile("barrier.cluster.arrive.relaxed.aligned;" ::: "memory"); }
__device__ __forceinline__ void cluster_wait() { asm volatile("barrier.cluster.wait.acquire.aligned;" ::: "memory"); }

__device__ __forceinline__ uint32_t wsel(const uint4& v, int i) { return i == 0 ? v.x : i == 1 ? v.y : i == 2 ? v.z : v.w; }
__device__ __forceinline__ int cmap(int j, int q, int e) { return j < 4 ? 8 * q + 2 * j + e : 32 + 4 * q + 2 * (j - 4) + e; }

struct DRow {
  uint32_t o0[6], o1[6];
};
struct PRow {
  uint4 a;
  uint2 b;
};
__device__ __forceinline__ uint32_t pw(const PRow& p, int j) {
  return j == 0 ? p.a.x : j == 1 ? p.a.y : j == 2 ? p.a.z : j == 3 ? p.a.w : j == 4 ? p.b.x : p.b.y;
}
template <bool ADD>
__device__ __forceinline__ uint32_t top(uint32_t a, uint32_t b) {
  return ADD ? hadd2(a, b) : hsub2(a, b);
}
template <bool ADD>
__device__ __forceinline__ void edges(uint32_t (&te)[6], uint32_t ra, uint32_t rb) {
  const uint4 a = lds128(ra), b = lds128(rb);
  const uint2 c = lds64(ra + 16), d = lds64(rb + 16);
  te[0] = top<ADD>(a.x, b.x);
  te[1] = top<ADD>(a.y, b.y);
  te[2] = top<ADD>(a.z, b.z);
  te[3] = top<ADD>(a.w, b.w);
  te[4] = top<ADD>(c.x, d.x);
  te[5] = top<ADD>(c.y, d.y);
}
template <bool ADD>
__device__ __forceinline__ void frags(uint32_t (&f)[12], const DRow& a, const DRow& b, const uint32_t (&te)[6], int ks,
                                      bool e0, bool e7) {
#pragma unroll
  for (int i = 0; i < 2; i++) {
    const int j = 2 * ks + i;
    const uint32_t t0 = top<ADD>(a.o0[j], b.o0[j]), t1 = top<ADD>(a.o1[j], b.o1[j]);
    const uint32_t nA = __shfl_up_sync(0xffffffffu, t1, 4);
    const uint32_t nB = __shfl_down_sync(0xffffffffu, t0, 4);
    f[0 + 2 * i] = e0 ? te[j] : nA;
    f[1 + 2 * i] = t0;
    f[4 + 2 * i] = t0;
    f[5 + 2 * i] = t1;
    f[8 + 2 * i] = t1;
    f[9 + 2 * i] = e7 ? te[j] : nB;
  }
}
template <int MODE>
__device__ __forceinline__ void fr1(uint32_t (&f)[12], const DRow& a, const DRow& b, int ks) {
#pragma unroll
  for (int i = 0; i < 2; i++) {
    const int j = 2 * ks + i;
    const uint32_t t0 = MODE == 0 ? a.o0[j] : top<MODE == 1>(a.o0[j], b.o0[j]);
    const uint32_t t1 = MODE == 0 ? a.o1[j] : top<MODE == 1>(a.o1[j], b.o1[j]);
    f[0 + 2 * i] = __shfl_up_sync(0xffffffffu, t1, 4);
    f[9 + 2 * i] = __shfl_down_sync(0xffffffffu, t0, 4);
    f[1 + 2 * i] = t0;
    f[4 + 2 * i] = t0;
    f[5 + 2 * i] = t1;
    f[8 + 2 * i] = t1;
  }
}
__device__ __forceinline__ void fr2(uint32_t (&f)[12], const uint32_t (&te)[6], int ks, bool e0, bool e7) {
#pragma unroll
  for (int i = 0; i < 2; i++) {
    f[0 + 2 * i] = e0 ? te[2 * ks + i] : f[0 + 2 * i];
    f[9 + 2 * i] = e7 ? te[2 * ks + i] : f[9 + 2 * i];
    asm volatile("" : "+r"(f[0 + 2 * i]), "+r"(f[9 + 2 * i]));
  }
}
struct ERaw {
  uint4 a, b;
  uint2 c, d;
};
__device__ __forceinline__ void ed1(ERaw& r, uint32_t ra, uint32_t rb) {
  r.a = lds128(ra);
  r.b = lds128(rb);
  r.c = lds64(ra + 16);
  r.d = lds64(rb + 16);
}
template <bool ADD>
__device__ __forceinline__ void ed2(uint32_t (&te)[6], const ERaw& r) {
  te[0] = top<ADD>(r.a.x, r.b.x);
  te[1] = top<ADD>(r.a.y, r.b.y);
  te[2] = top<ADD>(r.a.z, r.b.z);
  te[3] = top<ADD>(r.a.w, r.b.w);
  te[4] = top<ADD>(r.c.x, r.d.x);
  te[5] = top<ADD>(r.c.y, r.d.y);
}
template <int INIT>
__device__ __forceinline__ void conv_group(float (&acc)[48], const uint32_t (&f)[12], uint32_t dB, int pos, int ks) {
  wg_fence();
  wgmma_rs_n96<INIT>(acc, f[0], f[1], f[2], f[3], dB + (uint32_t)(((3 * pos + 0) * UT + 2 * ks * 1536) >> 4));
  wgmma_rs_n96<0>(acc, f[4], f[5], f[6], f[7], dB + (uint32_t)(((3 * pos + 1) * UT + 2 * ks * 1536) >> 4));
  wgmma_rs_n96<0>(acc, f[8], f[9], f[10], f[11], dB + (uint32_t)(((3 * pos + 2) * UT + 2 * ks * 1536) >> 4));
  wg_commit();
}
template <int CH, int INIT>
__device__ __forceinline__ void lateral(float (&acc)[24], uint32_t dA, uint32_t dwl) {
  wg_fence();
#pragma unroll
  for (int k = 0; k < 6; k++) {
    const uint32_t a = dA + (uint32_t)(((k >> 1) * CH + (k & 1) * 32) >> 4);
    const uint32_t b = dwl + (uint32_t)(k * 1536 >> 4);
    if (k == 0)
      wgmma_ss_n48<INIT>(acc, a, b);
    else
      wgmma_ss_n48<0>(acc, a, b);
  }
  wg_commit();
}

#define AI __attribute__((always_inline))
template <int V>
struct IC {
  static constexpr int value = V;
};

template <int RANK>
__device__ __forceinline__ void fpn_body(const CUtensorMap& map_row, const CUtensorMap& map_col,
                                         const __nv_bfloat16* __restrict__ p_coarse,
                                         const __nv_bfloat16* __restrict__ w_lat,
                                         const __nv_bfloat16* __restrict__ w_out, __nv_bfloat16* __restrict__ out) {
  extern __shared__ __align__(1024) unsigned char smem[];
  const uint32_t sb = (uint32_t)__cvta_generic_to_shared(smem);
  if ((sb & 0xFFFFFFu) != SB0) __trap();
  const int tid = threadIdx.x;
  const int wg = __shfl_sync(0xffffffffu, tid >> 7, 0);
  const int t128 = tid & 127;
  const int w = __shfl_sync(0xffffffffu, (tid >> 5) & 3, 0);
  const int lane = tid & 31;
  const int g = lane >> 2, q = lane & 3;
  constexpr uint32_t rank = RANK;
  const int cl = blockIdx.x >> 1;
  const int y0 = (cl >> 2) * 32;
  const int x0 = ((cl & 3) * 2 + wg) * 64;

  uint4 wv[8];
  const bool wl_thr = tid >= 32 && tid < 104;
  const int wl_kc = (tid - 32) / 6, wl_u = (tid - 32) % 6;
  if (wl_thr) {
#pragma unroll
    for (int kk = 0; kk < 8; kk++)
      wv[kk] = ldg128((const unsigned char*)w_lat + ((size_t)(8 * wl_kc + kk) * 96 + 48 * rank + 8 * wl_u) * 2);
  }
  uint32_t ticket = 0;
  if (tid >= 224) {
    const int idx = blockIdx.x * 14 + lane;
    if (lane < 14 && idx < 1728) {
      const int wd = idx & 3, t = idx >> 2, rk = t / 216, rem = t % 216, dj = rem / 72, kc = (rem % 72) / 12, u = rem % 12;
      const unsigned char* src = (const unsigned char*)w_out + ((size_t)(dj * 96 + 48 * rk) * 96 + 8 * u) * 2 + 4 * wd;
      uint32_t v[3][8];
#pragma unroll
      for (int kk = 0; kk < 8; kk++) {
        const int ci = cmap(kc, kk >> 1, kk & 1);
#pragma unroll
        for (int di = 0; di < 3; di++) v[di][kk] = __ldg((const uint32_t*)(src + (size_t)di * 3 * 96 * 192 + ci * 192));
      }
      uint32_t u0[2][4], u1[2][4], u2[2][4], u3[2][4];
#pragma unroll
      for (int kp = 0; kp < 4; kp++) {
        const uint32_t a0 = v[0][2 * kp], a1 = v[0][2 * kp + 1];
        const uint32_t b0 = v[1][2 * kp], b1 = v[1][2 * kp + 1];
        const uint32_t c0 = v[2][2 * kp], c1 = v[2][2 * kp + 1];
        u0[0][kp] = __byte_perm(a0, a1, 0x5410);
        u0[1][kp] = __byte_perm(a0, a1, 0x7632);
        u3[0][kp] = __byte_perm(c0, c1, 0x5410);
        u3[1][kp] = __byte_perm(c0, c1, 0x7632);
        const float s0l = bf_lo(a0) + bf_lo(c0), s1l = bf_lo(a1) + bf_lo(c1);
        const float s0h = bf_hi(a0) + bf_hi(c0), s1h = bf_hi(a1) + bf_hi(c1);
        u1[0][kp] = pack_bf16((s0l + bf_lo(b0)) * 0.5f, (s1l + bf_lo(b1)) * 0.5f);
        u1[1][kp] = pack_bf16((s0h + bf_hi(b0)) * 0.5f, (s1h + bf_hi(b1)) * 0.5f);
        u2[0][kp] = pack_bf16((s0l - bf_lo(b0)) * 0.5f, (s1l - bf_lo(b1)) * 0.5f);
        u2[1][kp] = pack_bf16((s0h - bf_hi(b0)) * 0.5f, (s1h - bf_hi(b1)) * 0.5f);
      }
      unsigned char* dst = g_u + rk * 12 * UT + dj * UT + kc * 1536 + (32 * (u >> 2) + 2 * (u & 3) + 8 * wd) * 16;
#pragma unroll
      for (int e = 0; e < 2; e++) {
        *(uint4*)(dst + e * 16) = make_uint4(u0[e][0], u0[e][1], u0[e][2], u0[e][3]);
        *(uint4*)(dst + e * 16 + 3 * UT) = make_uint4(u1[e][0], u1[e][1], u1[e][2], u1[e][3]);
        *(uint4*)(dst + e * 16 + 6 * UT) = make_uint4(u2[e][0], u2[e][1], u2[e][2], u2[e][3]);
        *(uint4*)(dst + e * 16 + 9 * UT) = make_uint4(u3[e][0], u3[e][1], u3[e][2], u3[e][3]);
      }
      asm volatile("fence.proxy.async.global;" ::: "memory");
    }
    __syncwarp();
    if (lane == 0) asm volatile("atom.release.gpu.global.add.u32 %0, [%1], 1;" : "=r"(ticket) : "l"(&g_cnt) : "memory");
  }
  if (tid == 0) {
#pragma unroll
    for (int i = 0; i < 2; i++) {
      const uint32_t b = sb + OFF_BAR + i * 64;
      mbar_init(b + 0, 1);
      mbar_init(b + 8, 1);
      mbar_init(b + 16, 1);
      mbar_init(b + 24, 1);
      mbar_init(b + 32, 4);
      mbar_init(b + 40, 4);
      mbar_init(b + 48, 1);
      mbar_init(b + 56, 4);
      mbar_init(sb + OFF_BAR + 128 + i * 16, 1);
      mbar_init(sb + OFF_BAR + 136 + i * 16, 1);
    }
    asm volatile("fence.mbarrier_init.release.cluster;" ::: "memory");
    fence_async_smem();
#pragma unroll
    for (int i = 0; i < 2; i++) {
      const uint32_t b = sb + OFF_BAR + i * 64;
      const int xw = ((cl & 3) * 2 + i) * 64;
      mbar_expect_tx(b + 48, 2 * HTILE);
      tma_col(sb + OFF_X + i * X_BYTES, &map_col, y0 - 1, xw - 1, b + 48);
      tma_col(sb + OFF_X + i * X_BYTES + HTILE, &map_col, y0 - 1, xw + 64, b + 48);
      mbar_expect_tx(b + 0, 2 * CSLOT);
      tma_row(sb + OFF_C + i * 2 * CSLOT, &map_row, (y0 - 1) * 32 + (xw >> 4), b + 0);
      tma_row(sb + OFF_H + i * HE_BYTES, &map_row, (y0 + 1) * 32 + (xw >> 4), b + 0);
      mbar_expect_tx(b + 8, CSLOT);
      tma_row(sb + OFF_C + i * 2 * CSLOT + CSLOT, &map_row, y0 * 32 + (xw >> 4), b + 8);
      mbar_expect_tx(b + 16, XROW);
      mbar_expect_tx(b + 24, XROW);
    }
  }
  cluster_arrive();

  if (wl_thr) {
    {
      const int kc = wl_kc, u = wl_u;
      const uint4(&v)[8] = wv;
#pragma unroll
      for (int wd = 0; wd < 4; wd++) {
        const int n = u < 4 ? 8 * wd + 2 * u : 8 * (4 + (wd & 1)) + 2 * (2 * (u - 4) + (wd >> 1));
        const uint32_t a = sb + OFF_WL + kc * 768 + n * 16;
        uint32_t lo[4], hi[4];
#pragma unroll
        for (int kp = 0; kp < 4; kp++) {
          lo[kp] = __byte_perm(wsel(v[2 * kp], wd), wsel(v[2 * kp + 1], wd), 0x5410);
          hi[kp] = __byte_perm(wsel(v[2 * kp], wd), wsel(v[2 * kp + 1], wd), 0x7632);
        }
        sts128(a, lo[0], lo[1], lo[2], lo[3]);
        sts128(a + 16, hi[0], hi[1], hi[2], hi[3]);
      }
    }
    fence_async_smem();
  }
  const unsigned char* pc = (const unsigned char*)p_coarse + 96 * rank;

  PRow hp[2][2], pA, pp;
  bool hv[2][2];
#pragma unroll
  for (int sd = 0; sd < 2; sd++)
#pragma unroll
    for (int h = 0; h < 2; h++) {
      const int hr = 16 * w + 8 * h + g, yy = y0 - 1 + hr, xx = sd ? x0 + 64 : x0 - 1;
      hv[sd][h] = hr < 34 && yy >= 0 && yy < IMG && xx >= 0 && xx < IMG;
      const unsigned char* a = pc + (hv[sd][h] ? ((size_t)(yy >> 1) * 256 + (xx >> 1)) * 192 : 0);
      hp[sd][h].a = ldg128(a + 16 * q);
      hp[sd][h].b = ldg64(a + 64 + 8 * q);
    }
  uint32_t poff = ((y0 >> 1) * 256 + (x0 >> 1) + 8 * w + g) * 192 + 16 * q;
  {
    const unsigned char* a = pc + poff - (y0 > 0 ? 49152 : 0);
    pA.a = ldg128(a);
    pA.b = ldg64(a + 64 - 8 * q);
    pp.a = ldg128(pc + poff);
    pp.b = ldg64(pc + poff + 64 - 8 * q);
    poff += 49152;
  }

  __syncthreads();
  cluster_wait();

  const uint32_t bb = sb + OFF_BAR + wg * 64;
  constexpr uint32_t dwl = make_desc(SB0 + OFF_WL, 768);
  constexpr uint32_t dB = make_desc(SB0 + OFF_U, 1536);
  const uint32_t cs = sb + OFF_C + wg * 2 * CSLOT;
  const uint32_t dC = make_desc(SB0 + OFF_C, 16) + wg * (2 * CSLOT >> 4);
  const uint32_t xbase = sb + OFF_X + wg * X_BYTES;
  const uint32_t dH = make_desc(SB0 + OFF_X, 16) + wg * (X_BYTES >> 4);
  const uint32_t hb = sb + OFF_H + wg * HE_BYTES;
  const uint32_t eb = hb + H_BYTES;
  const uint32_t ub = sb + OFF_BAR + 128;
  const uint32_t xa = xbase + t128 * 16;
  const uint32_t peer = rank ^ 1;
  const uint32_t rdelta = __shfl_sync(0xffffffffu, mapa(bb, peer) - bb, 0);
#define r_xa (xa + rdelta)
#define r_bb (bb + rdelta)
  const int grp0 = (y0 - 1) * 32 + (x0 >> 4);
  const bool last_block = (y0 + 32 == IMG);

  const bool e0 = g == 0, e7 = g == 7;
  const bool halo_lane = (w == 0 && g < 4) || (w == 3 && g >= 4);
  const uint32_t ewr = eb + (2 * w + (e7 ? 1 : 0)) * 512 + 32 * q;
  const uint32_t erd =
      (halo_lane ? (g < 4 ? hb : hb + HSIDE) : (g < 4 ? eb + (2 * w - 1) * 512 : eb + (2 * w + 2) * 512)) + 32 * q;
  const uint32_t emask = halo_lane ? 0xFFFFu : 511u;
  auto er = [&](int k) AI { return erd + (((uint32_t)k << 8) & emask); };

  float ax[48], ay[48], lat[24];
  DRow d1, d2, t0, t3;
  uint32_t f0[12], f1[12], f2[12], te[6], kp[12];
#pragma unroll
  for (int i = 0; i < 12; i++) kp[i] = 0;

  auto d_pack = [&](auto MODE, int i, DRow& d, DRow& t, const float(&acc)[24], const PRow& p, bool zero) AI {
    constexpr int mode = decltype(MODE)::value;
#pragma unroll
    for (int j = 0; j < 6; j++) {
      uint32_t n0 = hadd2(pack_bf16(acc[4 * j], acc[4 * j + 1]), pw(p, j));
      uint32_t n1 = hadd2(pack_bf16(acc[4 * j + 2], acc[4 * j + 3]), pw(p, j));
      if (zero) n0 = n1 = 0;
      if (mode == 1) {
        t.o0[j] = hsub2(n0, d.o0[j]);
        t.o1[j] = hsub2(n1, d.o1[j]);
      }
      if (mode == 2) {
        t.o0[j] = hsub2(d.o0[j], n0);
        t.o1[j] = hsub2(d.o1[j], n1);
      }
      d.o0[j] = n0;
      d.o1[j] = n1;
    }
    uint32_t ev[6];
#pragma unroll
    for (int j = 0; j < 6; j++) ev[j] = e0 ? d.o0[j] : d.o1[j];
    sts24_pred(ewr + (i & 3) * 128, ev, e0 || e7);
    if (mode != 0) {
      __syncwarp();
      if (lane == 0) mbar_arrive(bb + 56);
    }
  };
  auto refill = [&](int i) AI {
    if (t128 == 0 && i + 2 <= 33) {
      mbar_expect_tx(bb + (i & 1) * 8, CSLOT);
      tma_row(cs + (i & 1) * CSLOT, &map_row, grp0 + (i + 2) * 32, bb + (i & 1) * 8);
    }
  };
  auto send = [&](const float(&acc)[48], int b) AI {
    constexpr int rk = RANK;
#pragma unroll
    for (int J = 0; J < 3; J++) {
      uint32_t sd[4];
#pragma unroll
      for (int i = 0; i < 4; i++) {
        const int j = 4 * J + i;
        sd[i] = pack_bf16(acc[4 * j + 2 - 2 * rk], acc[4 * j + 3 - 2 * rk]);
        kp[j] = pack_bf16(acc[4 * j + 2 * rk], acc[4 * j + 2 * rk + 1]);
      }
      st_async128(r_xa + b * XROW + J * 2048, sd[0], sd[1], sd[2], sd[3], r_bb + 16 + 8 * b);
    }
  };
  unsigned char* op = (unsigned char*)out + (((y0 * IMG) + x0 + 16 * w + 2 * g + rank) * 192 + 16 * q) - 98304;
  uint4 xr[3];
  auto fin1 = [&](int b) AI {
#pragma unroll
    for (int J = 0; J < 3; J++) xr[J] = lds128(xa + b * XROW + J * 2048);
  };
  auto fin2 = [&](int b, uint32_t parity, uint32_t ok, bool more) AI {
    if (!ok) {
      mbar_wait(bb + 16 + 8 * b, parity);
      fin1(b);
    }
    if (more && t128 == 0) mbar_expect_tx(bb + 16 + 8 * b, XROW);
    op += 98304;
#pragma unroll
    for (int J = 0; J < 3; J++) {
      xr[J].x = hadd2(kp[4 * J + 0], xr[J].x);
      xr[J].y = hadd2(kp[4 * J + 1], xr[J].y);
      xr[J].z = hadd2(kp[4 * J + 2], xr[J].z);
      xr[J].w = hadd2(kp[4 * J + 3], xr[J].w);
      __stcs((uint4*)(op + 64 * J), xr[J]);
    }
    __syncwarp();
    if (more && lane == 0) mbar_arrive_remote(r_bb + 32 + 8 * b);
  };

  {
    float lat2[24], lr0[24], lr1[24], lr2[24];
    mbar_wait(bb + 48, 0);
    lateral<2560, 1>(lat, dH, dwl);
    lateral<2560, 1>(lat2, dH + (HTILE >> 4), dwl);
    mbar_wait(bb + 8, 0);
    lateral<4096, 1>(lr1, dC + (CSLOT >> 4), dwl);
    mbar_wait(bb + 0, 0);
    lateral<4096, 1>(lr0, dC, dwl);
    lateral<4096, 1>(lr2, make_desc(SB0 + OFF_H, 16) + wg * (HE_BYTES >> 4), dwl);
    if (tid == 224) {
      const uint32_t target = (ticket | 127u) + 1u;
      uint32_t c, n = 0;
      do {
        asm volatile("ld.acquire.gpu.global.u32 %0, [%1];" : "=r"(c) : "l"(&g_cnt) : "memory");
        if (++n > (1u << 22)) __trap();
      } while ((int)(c - target) < 0);
      asm volatile("fence.proxy.async.global;" ::: "memory");
#pragma unroll
      for (int i = 0; i < 4; i++) {
        const int pos = i == 0 ? 1 : i == 1 ? 2 : i == 2 ? 0 : 3;
        mbar_expect_tx(ub + 8 * pos, 3 * UT);
        bulk_load(sb + OFF_U + pos * 3 * UT, g_u + (rank * 12 + pos * 3) * UT, 3 * UT, ub + 8 * pos);
      }
    }
    __syncwarp();
    wg_wait<0>();
    fence_regs(lat);
    fence_regs(lat2);
    fence_regs(lr0);
    fence_regs(lr1);
    fence_regs(lr2);
    asm volatile("bar.sync %0, 128;" ::"r"(wg + 1) : "memory");
    refill(1);
    refill(2);
    __syncwarp();
    if (lane == 0) {
      mbar_arrive_remote(r_bb + 32);
      mbar_arrive_remote(r_bb + 40);
    }
#pragma unroll
    for (int h = 0; h < 2; h++) {
      const int hr = 16 * w + 8 * h + g;
      uint32_t v0[6], v1[6];
#pragma unroll
      for (int j = 0; j < 6; j++) {
        v0[j] = hv[0][h] ? hadd2(pack_bf16(lat[4 * j + 2 * h], lat[4 * j + 2 * h + 1]), pw(hp[0][h], j)) : 0u;
        v1[j] = hv[1][h] ? hadd2(pack_bf16(lat2[4 * j + 2 * h], lat2[4 * j + 2 * h + 1]), pw(hp[1][h], j)) : 0u;
      }
      sts24_pred(hb + hr * 128 + 32 * q, v0, hr < 34);
      sts24_pred(hb + HSIDE + hr * 128 + 32 * q, v1, hr < 34);
    }
    d_pack(IC<0>{}, 0, d2, t0, lr0, pA, y0 == 0);
    d_pack(IC<0>{}, 1, d1, t3, lr1, pp, false);
    d_pack(IC<2>{}, 2, d2, t0, lr2, pp, false);
    mbar_wait(bb + 56, 0);
    pp.a = ldg128(pc + poff);
    pp.b = ldg64(pc + poff + 64 - 8 * q);
    edges<true>(te, er(0) + 128, er(1));
    frags<true>(f0, d1, d2, te, 0, e0, e7);
    mbar_wait(ub + 8, 0);
    conv_group<1>(ax, f0, dB, 1, 0);
    frags<true>(f1, d1, d2, te, 1, e0, e7);
  }

  ERaw er4;
  uint32_t ok1, ok2;
#define CUT sched_cut<__LINE__>(cl)
  auto stepA = [&](auto FIRST, int s) AI {
    constexpr bool notfirst = !decltype(FIRST)::value;
    const uint32_t par = s & 1;
    wg_wait<1>();
    if (notfirst) fence_regs(ay);
    CUT;
    fr1<1>(f2, d1, d2, 2);
    if (notfirst && ok1) fin1(0);
    CUT;
    conv_group<0>(ax, f1, dB, 1, 1);
    CUT;
    if (notfirst) fin2(0, par ^ 1, ok1, true);
    fr2(f2, te, 2, e0, e7);
    wg_wait<1>();
    CUT;
    ed1(er4, er(s + 1), er(s) + 128);
    fr1<2>(f0, d2, d1, 0);
    if (notfirst) ok2 = mbar_try(bb + 40, par ^ 1);
    CUT;
    conv_group<0>(ax, f2, dB, 1, 2);
    CUT;
    if (notfirst) {
      if (!ok2) mbar_wait(bb + 40, par ^ 1);
      send(ay, 1);
    }
    ed2<false>(te, er4);
    fr2(f0, te, 0, e0, e7);
    wg_wait<1>();
    CUT;
    fr1<2>(f1, d2, d1, 1);
    if (!notfirst) mbar_wait(ub + 16, 0);
    CUT;
    conv_group<notfirst ? 2 : 1>(ay, f0, dB, 2, 0);
    CUT;
    fr2(f1, te, 1, e0, e7);
    wg_wait<1>();
    CUT;
    fr1<2>(f2, d2, d1, 2);
    CUT;
    conv_group<0>(ay, f1, dB, 2, 1);
    CUT;
    fr2(f2, te, 2, e0, e7);
    wg_wait<1>();
    CUT;
    ed1(er4, er(s), er(s + 1));
    fr1<0>(f0, t0, t0, 0);
    ok1 = mbar_try(bb + 8, par ^ 1);
    CUT;
    conv_group<0>(ay, f2, dB, 2, 2);
    CUT;
    ed2<false>(te, er4);
    fr2(f0, te, 0, e0, e7);
    if (!ok1) mbar_wait(bb + 8, par ^ 1);
    wg_wait<1>();
    CUT;
    fr1<0>(f1, t0, t0, 1);
    CUT;
    lateral<4096, 2>(lat, dC + (CSLOT >> 4), dwl);
    CUT;
    fr2(f1, te, 1, e0, e7);
    if (!notfirst) {
      mbar_wait(ub + 0, 0);
      mbar_wait(ub + 24, 0);
    }
    CUT;
    wg_wait<1>();
    fence_regs(ax);
    fence_regs(ay);
  };
  auto stepB = [&](auto LAST, int s) AI {
    constexpr bool notlast = !decltype(LAST)::value;
    const uint32_t par = s & 1;
    fr1<0>(f2, t0, t0, 2);
    if (notlast) ok2 = mbar_try(bb + 0, par ^ 1);
    ok1 = mbar_try(bb + 24, par ^ 1);
    CUT;
#pragma unroll
    for (int i = 0; i < 48; i++) {
      asm volatile("add.f32 %0, %0, %1;\n\tfma.rn.f32 %1, %1, 0fC0000000, %0;" : "+f"(ax[i]), "+f"(ay[i]));
    }
    fence_regs(ax);
    fence_regs(ay);
    conv_group<0>(ax, f0, dB, 0, 0);
    wg_wait<1>();
    fence_regs(lat);
    CUT;
    d_pack(IC<1>{}, 2 * s + 3, d1, t3, lat, pp, last_block && !notlast);
    fr2(f2, te, 2, e0, e7);
    if (notlast && !ok2) mbar_wait(bb + 0, par ^ 1);
    if (ok1) fin1(1);
    CUT;
    if (notlast) lateral<4096, 2>(lat, dC, dwl);
    CUT;
    if (s > 0) fin2(1, par ^ 1, ok1, true);
    wg_wait<notlast ? 1 : 0>();
    CUT;
    ok1 = mbar_try(bb + 56, 1);
    fr1<0>(f0, t3, t3, 0);
    CUT;
    conv_group<0>(ax, f1, dB, 0, 1);
    CUT;
    if (!ok1) mbar_wait(bb + 56, 1);
    refill(2 * s + 3);
    if (notlast) {
      wg_wait<1>();
      fence_regs(lat);
      CUT;
    }
    ed1(er4, er(s + 1) + 128, er(s) + 128);
    if (notlast) {
      d_pack(IC<2>{}, 2 * s + 4, d2, t0, lat, pp, false);
      if ((y0 >> 1) + s + 2 < 256) poff += 49152;
      pp.a = ldg128(pc + poff);
      pp.b = ldg64(pc + poff + 64 - 8 * q);
    }
    CUT;
    conv_group<0>(ax, f2, dB, 0, 2);
    CUT;
    ed2<false>(te, er4);
    fr2(f0, te, 0, e0, e7);
    wg_wait<1>();
    keep(f1);
    CUT;
    fr1<0>(f1, t3, t3, 1);
    if (notlast) ok1 = mbar_try(bb + 56, 0);
    CUT;
    conv_group<0>(ay, f0, dB, 3, 0);
    CUT;
    fr2(f1, te, 1, e0, e7);
    if (notlast) {
      if (!ok1) mbar_wait(bb + 56, 0);
      refill(2 * s + 4);
    }
    wg_wait<1>();
    fence_regs(ax);
    keep(f2);
    CUT;
    fr1<0>(f2, t3, t3, 2);
    ok2 = mbar_try(bb + 32, par);
    CUT;
    conv_group<0>(ay, f1, dB, 3, 1);
    CUT;
    if (!ok2) mbar_wait(bb + 32, par);
    send(ax, 0);
    fr2(f2, te, 2, e0, e7);
    if (notlast) {
      wg_wait<1>();
      CUT;
      ed1(er4, er(s + 1) + 128, er(s + 2));
      fr1<1>(f0, d1, d2, 0);
    }
    CUT;
    conv_group<0>(ay, f2, dB, 3, 2);
    if (notlast) {
      CUT;
      ed2<true>(te, er4);
      fr2(f0, te, 0, e0, e7);
      wg_wait<1>();
      CUT;
      fr1<1>(f1, d1, d2, 1);
      ok1 = mbar_try(bb + 16, par);
      CUT;
      conv_group<2>(ax, f0, dB, 1, 0);
      CUT;
      fr2(f1, te, 1, e0, e7);
    }
  };

  stepA(IC<1>{}, 0);
#pragma unroll 1
  for (int s = 0; s < NSTEP - 1; s++) {
    stepB(IC<0>{}, s);
    stepA(IC<0>{}, s + 1);
  }
  stepB(IC<1>{}, NSTEP - 1);
  fin2(0, 1, 0, false);
  wg_wait<0>();
  fence_regs(ay);
  mbar_wait(bb + 40, 1);
  send(ay, 1);
  fin2(1, 1, 0, false);
}

__global__ void __cluster_dims__(2, 1, 1) __launch_bounds__(256, 1)
    fpn_kernel(const __grid_constant__ CUtensorMap map_row, const __grid_constant__ CUtensorMap map_col,
               const __nv_bfloat16* __restrict__ p_coarse, const __nv_bfloat16* __restrict__ w_lat,
               const __nv_bfloat16* __restrict__ w_out, __nv_bfloat16* __restrict__ out) {
  uint32_t rank;
  asm("mov.u32 %0, %%cluster_ctarank;" : "=r"(rank));
  if (rank)
    fpn_body<1>(map_row, map_col, p_coarse, w_lat, w_out, out);
  else
    fpn_body<0>(map_row, map_col, p_coarse, w_lat, w_out, out);
}

typedef CUresult (*EncodeFn)(CUtensorMap*, CUtensorMapDataType, cuuint32_t, void*, const cuuint64_t*, const cuuint64_t*,
                             const cuuint32_t*, const cuuint32_t*, CUtensorMapInterleave, CUtensorMapSwizzle,
                             CUtensorMapL2promotion, CUtensorMapFloatOOBfill);

}

extern "C" void kernel_launch(void* const* d_in, const int* in_sizes, int n_in, void* d_out, int out_size) {
  (void)in_sizes;
  (void)n_in;
  (void)out_size;
  static EncodeFn encode = nullptr;
  if (!encode) {
    cudaFuncSetAttribute(fpn_kernel, cudaFuncAttributeMaxDynamicSharedMemorySize, SMEM_BYTES);
    void* fn = nullptr;
    cudaDriverEntryPointQueryResult st;
    cudaGetDriverEntryPoint("cuTensorMapEncodeTiled", &fn, cudaEnableDefault, &st);
    encode = (EncodeFn)fn;
  }
  CUtensorMap map_row, map_col;
  {
    const cuuint64_t dim[5] = {32, 8, 2, 16384, 3};
    const cuuint64_t str[4] = {384, 192, 3072, 64};
    const cuuint32_t box[5] = {32, 8, 2, 4, 3};
    const cuuint32_t es[5] = {1, 1, 1, 1, 1};
    encode(&map_row, CU_TENSOR_MAP_DATA_TYPE_BFLOAT16, 5, d_in[0], dim, str, box, es, CU_TENSOR_MAP_INTERLEAVE_NONE,
           CU_TENSOR_MAP_SWIZZLE_64B, CU_TENSOR_MAP_L2_PROMOTION_L2_128B, CU_TENSOR_MAP_FLOAT_OOB_FILL_NONE);
  }
  {
    const cuuint64_t dim[4] = {32, 512, 3, 512};
    const cuuint64_t str[3] = {98304, 64, 192};
    const cuuint32_t box[4] = {32, 40, 3, 1};
    const cuuint32_t es[4] = {1, 1, 1, 1};
    encode(&map_col, CU_TENSOR_MAP_DATA_TYPE_BFLOAT16, 4, d_in[0], dim, str, box, es, CU_TENSOR_MAP_INTERLEAVE_NONE,
           CU_TENSOR_MAP_SWIZZLE_64B, CU_TENSOR_MAP_L2_PROMOTION_L2_64B, CU_TENSOR_MAP_FLOAT_OOB_FILL_NONE);
  }
  fpn_kernel<<<128, 256, SMEM_BYTES, cudaStreamPerThread>>>(map_row, map_col, (const __nv_bfloat16*)d_in[1],
                                                            (const __nv_bfloat16*)d_in[2], (const __nv_bfloat16*)d_in[3],
                                                            (__nv_bfloat16*)d_out);
}
```
